```python
import torch

def _softmax(x, axis=-1):
    return torch.softmax(x, dim=axis)
def _gelu(x):
    return torch.nn.functional.gelu(x, approximate="tanh")
def _silu(x):
    return torch.nn.functional.silu(x)
def _sigmoid(x):
    return torch.sigmoid(x)
def _layernorm(x, axis=-1, eps=1e-5):
    m = x.mean(dim=axis, keepdim=True)
    v = x.var(dim=axis, keepdim=True, unbiased=False)
    return (x - m) / torch.sqrt(v + eps)
def _scatter_add(tgt, idx, src, axis=0):
    return tgt.clone().index_add_(axis, idx, src)
def _segment_sum(src, seg, n):
    out = torch.zeros((n,) + src.shape[1:], dtype=src.dtype)
    return out.index_add_(0, seg, src)
def _pad(x, pw):
    flat = tuple(v for pair in reversed(pw) for v in pair)
    return torch.nn.functional.pad(x, flat)

kernel_name = 'sequential_preLN__ssm_conv_s4__glu_gated_swiglu__prompt'

def setup_inputs():

    _w = (lambda a: (lambda t: t.to(torch.bfloat16) if t.is_floating_point() else t)(torch.as_tensor(a)))
    def _A_setup():
        B, L, D, N = 1, 2048, 576, 128
        A_re = -(lambda _x: torch.exp(torch.as_tensor(_x)))((lambda *s: torch.randn(*s, dtype=torch.bfloat16) * 6.4)(D, N))
        A_im = torch.pi * (lambda *s: torch.randn(*s, dtype=torch.bfloat16) * 0.05)(D, N)
        B_re = (lambda *s: torch.randn(*s, dtype=torch.bfloat16) * 0.05)(D, N)
        B_im = (lambda *s: torch.randn(*s, dtype=torch.bfloat16) * 0.05)(D, N)
        C_re = (lambda *s: torch.randn(*s, dtype=torch.bfloat16) * 0.05)(D, N)
        C_im = (lambda *s: torch.randn(*s, dtype=torch.bfloat16) * 0.05)(D, N)
        log_dt = (lambda *s: torch.randn(*s, dtype=torch.bfloat16) * 0.05)(D) * 0.5 - 4.0
        Dskip = (lambda *s: torch.randn(*s, dtype=torch.bfloat16) * 0.05)(D)
        return {
            "u": _w((lambda *s: torch.randn(*s, dtype=torch.bfloat16) * 0.05)(B, L, D)),
            "A_re": _w(A_re),
            "A_im": _w(A_im),
            "B_re": _w(B_re),
            "B_im": _w(B_im),
            "C_re": _w(C_re),
            "C_im": _w(C_im),
            "log_dt": _w(log_dt),
            "Dskip": _w(Dskip),
        }
    _A_in = _A_setup()

    def _B_setup():
        B, S, D, F = 1, 2048, 576, 4608
        return {
            "x": _w((lambda *s: torch.randn(*s, dtype=torch.bfloat16) * 0.05)(B, S, D)),
            "w1": _w((lambda *s: torch.randn(*s, dtype=torch.bfloat16) * 0.4)(D, F) * (2.0 / D) ** 0.5),
            "w3": _w((lambda *s: torch.randn(*s, dtype=torch.bfloat16) * 0.4)(D, F) * (2.0 / D) ** 0.5),
            "w2": _w((lambda *s: torch.randn(*s, dtype=torch.bfloat16) * 0.4)(F, D) * (2.0 / F) ** 0.5),
        }
    _B_in = _B_setup()

    return {
        "A_u": _A_in["u"],
        "A_A_re": _A_in["A_re"],
        "A_A_im": _A_in["A_im"],
        "A_B_re": _A_in["B_re"],
        "A_B_im": _A_in["B_im"],
        "A_C_re": _A_in["C_re"],
        "A_C_im": _A_in["C_im"],
        "A_log_dt": _A_in["log_dt"],
        "A_Dskip": _A_in["Dskip"],
        "B_x": _B_in["x"],
        "B_w1": _B_in["w1"],
        "B_w3": _B_in["w3"],
        "B_w2": _B_in["w2"],
    }

def reference(A_u, A_A_re, A_A_im, A_B_re, A_B_im, A_C_re, A_C_im, A_log_dt, A_Dskip, B_x, B_w1, B_w3, B_w2):
    def _A_ref(u, A_re, A_im, B_re, B_im, C_re, C_im, log_dt, Dskip):
        Bsz, L, D = u.shape
        dt = torch.exp(log_dt)[:, None]
        A = A_re + 1j * A_im
        Bc = B_re + 1j * B_im
        Cc = C_re + 1j * C_im
        logdA = dt * A
        dB = dt * Bc
        l = (lambda x, dt: x.to(dt))(torch.arange(L), A_re.dtype)
        P = torch.exp(logdA[:, :, None] * l[None, None, :])
        K = torch.einsum("dn,dnl,dn->dl", Cc, P, dB).real
        L2 = 2 * L
        Kp = _pad(K, ((0, 0), (0, L)))
        up = (lambda x, *d: x.permute(*d))(u, 0, 2, 1)
        up = _pad(up, ((0, 0), (0, 0), (0, L)))
        Kf = (lambda x, axes=(-2,-1): torch.fft.rfft2(x.float(), dim=axes))(Kp[:, None, :], axes=(-2, -1))
        Uf = (lambda x, axes=(-2,-1): torch.fft.rfft2(x.float(), dim=axes))(up[:, :, None, :], axes=(-2, -1))
        Yf = Uf * Kf[None, :, :, :]
        y = (lambda x, s, axes=(-2,-1): torch.fft.irfft2(x, s=s, dim=axes).to(torch.bfloat16))(Yf, (1, L2), axes=(-2, -1))[:, :, 0, :L]
        y = (lambda x, *d: x.permute(*d))(y, 0, 2, 1) + u * Dskip[None, None, :]
        return y

    def _B_ref(x, w1, w3, w2):
        gate = torch.einsum("bsd,df->bsf", x, w1)
        up = torch.einsum("bsd,df->bsf", x, w3)
        h = _silu(gate) * up
        out = torch.einsum("bsf,fd->bsd", h, w2)
        return out

    x = A_u
    h = x + _A_ref(_layernorm(x, axis=-1), A_A_re, A_A_im, A_B_re, A_B_im, A_C_re, A_C_im, A_log_dt, A_Dskip)
    h2 = h + _B_ref(_layernorm(h, axis=-1), B_w1, B_w3, B_w2)
    return h2
```

```cpp
#include <cuda_runtime.h>
#include <cuda_bf16.h>
#include <cuda.h>
#include <stdint.h>

#define LAG1 4
#define LAG2 3
#define LAG3 3
#define HMC 0
#define PACE 2048

namespace {

constexpr int L = 2048, D = 576, F = 4608, NMODE = 128;
constexpr int NS = 6;
constexpr uint32_t SLOT = 16384, BOX = 8192;
constexpr uint32_t OFF_STASH = NS * SLOT;
constexpr uint32_t OFF_BAR = OFF_STASH + 16 * BOX;
constexpr uint32_t B_FULL = OFF_BAR, B_EMPTY = B_FULL + 8 * NS, B_H = B_EMPTY + 8 * NS, B_SF = B_H + 8 * 6,
                   B_SE = B_SF + 8 * 8, B_XIN = B_SE + 8 * 4, B_PRDY = B_XIN + 8 * 8, B_LIN = B_PRDY + 8 * 2,
                   B_B8 = B_LIN + 8 * 4, B_G = B_B8 + 8, B_UX = B_G + 8 * 4, B_END = B_UX + 8;
constexpr uint32_t OFF_MISC = OFF_BAR + 768;
constexpr uint32_t SMEM_BYTES = OFF_BAR + 1024;
constexpr uint32_t SPIN_LIMIT = 1u << 24;
static_assert(B_END <= OFF_BAR + 512, "barrier region");

constexpr uint32_t OFF_G = 0;
constexpr uint32_t OFF_WS = 2 * SLOT, WS_BYTES = 32768, WS_WARP = 7168, WS_KC = 4 * WS_WARP + 16;
constexpr uint32_t OFF_U = OFF_WS + 3 * WS_BYTES, U_PITCH = 4288;
constexpr uint32_t OFF_X = OFF_U + 5 * U_PITCH, X_PITCH = 4160;
constexpr uint32_t OFF_PK = OFF_X + 5 * X_PITCH, PK_PITCH = 8224;
static_assert(OFF_PK + 5 * PK_PITCH <= OFF_BAR, "front region");

__device__ __align__(1024) __nv_bfloat16 g_hT[D * L];
__device__ __align__(1024) uint4 g_part[16 * 8 * 3 * 2 * 512];
__device__ __align__(1024) uint4 g_part8[16 * 8 * 2 * 512];
__device__ __align__(128) uint4 g_stats[256 * 3];
__device__ unsigned g_flag[16 * 8 * 3 * 2];
__device__ unsigned g_flag8[16 * 8];
__device__ unsigned g_epoch;
#define STAMP(i)
#define STAMPC(c, i)

__device__ __forceinline__ void mbar_init(uint32_t b, uint32_t c) {
  asm volatile("mbarrier.init.shared::cta.b64 [%0], %1;" ::"r"(b), "r"(c));
}
__device__ __forceinline__ void mbar_expect(uint32_t b, uint32_t n) {
  asm volatile("mbarrier.arrive.expect_tx.shared::cta.b64 _, [%0], %1;" ::"r"(b), "r"(n) : "memory");
}
__device__ __forceinline__ void mbar_arrive(uint32_t b) {
  asm volatile("mbarrier.arrive.shared::cta.b64 _, [%0];" ::"r"(b) : "memory");
}
__device__ __forceinline__ void mbar_arrive_cluster(uint32_t b) {
  asm volatile("mbarrier.arrive.release.cluster.shared::cluster.b64 _, [%0];" ::"r"(b) : "memory");
}
__device__ __forceinline__ void mbar_wait(uint32_t b, uint32_t parity) {
  asm volatile(
      "{\n.reg .pred p;\n.reg .u32 c;\n"
      "mbarrier.try_wait.parity.shared::cta.b64 p, [%0], %1;\n@p bra DONE;\n"
      "mov.u32 c, 0;\n"
      "WAIT:\nmbarrier.try_wait.parity.shared::cta.b64 p, [%0], %1;\n@p bra DONE;\n"
      "add.u32 c, c, 1;\nsetp.lt.u32 p, c, %2;\n@p bra WAIT;\ntrap;\n"
      "DONE:\n}\n" ::"r"(b), "r"(parity), "n"(SPIN_LIMIT) : "memory");
}
__device__ __forceinline__ bool elect_one() {
  uint32_t p;
  asm volatile("{\n.reg .pred p;\nelect.sync _|p, 0xffffffff;\nselp.u32 %0, 1, 0, p;\n}\n" : "=r"(p));
  return p != 0;
}
__device__ __forceinline__ void tma2d(uint32_t dst, const CUtensorMap* m, int c0, int c1, uint32_t bar) {
  asm volatile("cp.async.bulk.tensor.2d.shared::cluster.global.mbarrier::complete_tx::bytes [%0], [%1, {%3, %4}], [%2];"
               ::"r"(dst), "l"(m), "r"(bar), "r"(c0), "r"(c1) : "memory");
}
__device__ __forceinline__ void tma2d_mc(uint32_t dst, const CUtensorMap* m, int c0, int c1, uint32_t bar) {
  asm volatile(
      "cp.async.bulk.tensor.2d.shared::cluster.global.mbarrier::complete_tx::bytes.multicast::cluster [%0], [%1, {%3, %4}], [%2], %5;"
      ::"r"(dst), "l"(m), "r"(bar), "r"(c0), "r"(c1), "h"((uint16_t)3) : "memory");
}
__device__ __forceinline__ void bulk_load(uint32_t dst, const void* src, uint32_t bytes, uint32_t bar) {
  asm volatile("cp.async.bulk.shared::cluster.global.mbarrier::complete_tx::bytes [%0], [%1], %2, [%3];"
               ::"r"(dst), "l"(src), "r"(bytes), "r"(bar) : "memory");
}
__device__ __forceinline__ void bulk_store(void* dst, uint32_t src, uint32_t bytes) {
  asm volatile("cp.async.bulk.global.shared::cta.bulk_group [%0], [%1], %2;" ::"l"(dst), "r"(src), "r"(bytes) : "memory");
}
__device__ __forceinline__ void ldsm4t(uint32_t* r, uint32_t a) {
  asm volatile("ldmatrix.sync.aligned.m8n8.x4.trans.shared.b16 {%0,%1,%2,%3}, [%4];"
               : "=r"(r[0]), "=r"(r[1]), "=r"(r[2]), "=r"(r[3]) : "r"(a) : "memory");
}
__device__ __forceinline__ void ldsm4(uint32_t* r, uint32_t a) {
  asm volatile("ldmatrix.sync.aligned.m8n8.x4.shared.b16 {%0,%1,%2,%3}, [%4];"
               : "=r"(r[0]), "=r"(r[1]), "=r"(r[2]), "=r"(r[3]) : "r"(a) : "memory");
}
__device__ __forceinline__ void ldsm2t(uint32_t* r, uint32_t a) {
  asm volatile("ldmatrix.sync.aligned.m8n8.x2.trans.shared.b16 {%0,%1}, [%2];" : "=r"(r[0]), "=r"(r[1]) : "r"(a) : "memory");
}
__device__ __forceinline__ void st_async128(uint32_t a, const uint32_t* r, uint32_t bar) {
  asm volatile("st.async.weak.shared::cluster.mbarrier::complete_tx::bytes.v4.b32 [%0], {%1,%2,%3,%4}, [%5];"
               ::"r"(a), "r"(r[0]), "r"(r[1]), "r"(r[2]), "r"(r[3]), "r"(bar) : "memory");
}
__device__ __forceinline__ uint32_t mapa(uint32_t a, uint32_t rank) {
  uint32_t r;
  asm("mapa.shared::cluster.u32 %0, %1, %2;" : "=r"(r) : "r"(a), "r"(rank));
  return r;
}
__device__ __forceinline__ uint32_t lds32(uint32_t a) {
  uint32_t r;
  asm volatile("ld.shared.b32 %0, [%1];" : "=r"(r) : "r"(a) : "memory");
  return r;
}
__device__ __forceinline__ uint32_t lds16(uint32_t a) {
  uint32_t r;
  asm volatile("ld.shared.u16 %0, [%1];" : "=r"(r) : "r"(a) : "memory");
  return r;
}
__device__ __forceinline__ void lds64(uint32_t* r, uint32_t a) {
  asm volatile("ld.shared.v2.b32 {%0,%1}, [%2];" : "=r"(r[0]), "=r"(r[1]) : "r"(a) : "memory");
}
__device__ __forceinline__ void sts32(uint32_t a, uint32_t v) {
  asm volatile("st.shared.b32 [%0], %1;" ::"r"(a), "r"(v) : "memory");
}
__device__ __forceinline__ void sts16(uint32_t a, uint32_t v) {
  asm volatile("st.shared.u16 [%0], %1;" ::"r"(a), "r"(v) : "memory");
}
__device__ __forceinline__ void mma_bf16(float* c, uint32_t a0, uint32_t a1, uint32_t a2, uint32_t a3, const uint32_t* b) {
  asm volatile("mma.sync.aligned.m16n8k16.row.col.f32.bf16.bf16.f32 {%0,%1,%2,%3}, {%4,%5,%6,%7}, {%8,%9}, {%0,%1,%2,%3};"
               : "+f"(c[0]), "+f"(c[1]), "+f"(c[2]), "+f"(c[3])
               : "r"(a0), "r"(a1), "r"(a2), "r"(a3), "r"(b[0]), "r"(b[1]));
}
__device__ __forceinline__ void wg_bar(int wg) { asm volatile("bar.sync %0, 128;" ::"r"(wg + 1) : "memory"); }
__device__ __forceinline__ void stsm4(uint32_t a, const uint32_t* r) {
  asm volatile("stmatrix.sync.aligned.m8n8.x4.shared.b16 [%0], {%1,%2,%3,%4};"
               ::"r"(a), "r"(r[0]), "r"(r[1]), "r"(r[2]), "r"(r[3]) : "memory");
}
__device__ __forceinline__ void sts128(uint32_t a, const uint32_t* r) {
  asm volatile("st.shared.v4.b32 [%0], {%1,%2,%3,%4};" ::"r"(a), "r"(r[0]), "r"(r[1]), "r"(r[2]), "r"(r[3]) : "memory");
}
__device__ __forceinline__ void lds128(uint32_t* r, uint32_t a) {
  asm volatile("ld.shared.v4.b32 {%0,%1,%2,%3}, [%4];" : "=r"(r[0]), "=r"(r[1]), "=r"(r[2]), "=r"(r[3]) : "r"(a) : "memory");
}
__device__ __forceinline__ uint32_t pack_bf16(float lo, float hi) {
  uint32_t r;
  asm("cvt.rn.bf16x2.f32 %0, %1, %2;" : "=r"(r) : "f"(hi), "f"(lo));
  return r;
}
__device__ __forceinline__ float bf_lo(uint32_t v) { return __uint_as_float(v << 16); }
__device__ __forceinline__ float bf_hi(uint32_t v) { return __uint_as_float(v & 0xffff0000u); }
__device__ __forceinline__ float round_bf16(float v) { return __bfloat162float(__float2bfloat16_rn(v)); }
__device__ __forceinline__ uint32_t sub_bf16x2(uint32_t a, uint32_t b) {
  uint32_t r;
  asm("sub.rn.bf16x2 %0, %1, %2;" : "=r"(r) : "r"(a), "r"(b));
  return r;
}
__device__ __forceinline__ uint32_t add_bf16x2(uint32_t a, uint32_t b) {
  uint32_t r;
  asm("add.rn.bf16x2 %0, %1, %2;" : "=r"(r) : "r"(a), "r"(b));
  return r;
}
__device__ __forceinline__ uint32_t mul_bf16x2(uint32_t a, uint32_t b) {
  uint32_t r;
  asm("mul.rn.bf16x2 %0, %1, %2;" : "=r"(r) : "r"(a), "r"(b));
  return r;
}
__device__ __forceinline__ uint32_t fma_bf16x2(uint32_t a, uint32_t b, uint32_t c) {
  uint32_t r;
  asm("fma.rn.bf16x2 %0, %1, %2, %3;" : "=r"(r) : "r"(a), "r"(b), "r"(c));
  return r;
}
__device__ __forceinline__ float ln_rstd(float var) {
  float sd, r;
  asm("sqrt.approx.f32 %0, %1;" : "=f"(sd) : "f"(round_bf16(round_bf16(var) + 1e-5f)));
  asm("rcp.approx.f32 %0, %1;" : "=f"(r) : "f"(round_bf16(sd)));
  return r;
}
__device__ __forceinline__ float tanh_hw(float x) {
  float r;
  asm("tanh.approx.f32 %0, %1;" : "=f"(r) : "f"(x));
  return r;
}
__device__ __forceinline__ unsigned ld_acquire(const unsigned* p) {
  unsigned v;
  asm volatile("ld.acquire.gpu.global.u32 %0, [%1];" : "=r"(v) : "l"(p) : "memory");
  return v;
}
__device__ __forceinline__ void wait_flag(const unsigned* p, unsigned target) {
  uint32_t c = 0;
  while ((int)(ld_acquire(p) - target) < 0) {
    if (++c > SPIN_LIMIT) __trap();
  }
}
__device__ __forceinline__ void red_add(unsigned* p, unsigned v) {
  asm volatile("red.relaxed.gpu.global.add.u32 [%0], %1;" ::"l"(p), "r"(v) : "memory");
}
#define WG_FENCE() asm volatile("wgmma.fence.sync.aligned;" ::: "memory")
#define WG_COMMIT() asm volatile("wgmma.commit_group.sync.aligned;" ::: "memory")
#define WG_WAIT(n) asm volatile("wgmma.wait_group.sync.aligned %0;" ::"n"(n) : "memory")

__device__ __forceinline__ void wgmma_rs_n128(float (&d)[64], const uint32_t* a, uint64_t db, int accum) {
  asm volatile(
      "{\n.reg .pred p;\nsetp.ne.b32 p, %69, 0;\n"
      "wgmma.mma_async.sync.aligned.m64n128k16.f32.bf16.bf16 "
      "{%0,%1,%2,%3,%4,%5,%6,%7,%8,%9,%10,%11,%12,%13,%14,%15,%16,%17,%18,%19,%20,%21,%22,%23,%24,%25,%26,%27,%28,%29,%30,%31,%32,%33,%34,%35,%36,%37,%38,%39,%40,%41,%42,%43,%44,%45,%46,%47,%48,%49,%50,%51,%52,%53,%54,%55,%56,%57,%58,%59,%60,%61,%62,%63}, "
      "{%64,%65,%66,%67}, %68, p, 1, 1, 1;\n}\n"
      : "+f"(d[0]), "+f"(d[1]), "+f"(d[2]), "+f"(d[3]), "+f"(d[4]), "+f"(d[5]), "+f"(d[6]), "+f"(d[7]),
        "+f"(d[8]), "+f"(d[9]), "+f"(d[10]), "+f"(d[11]), "+f"(d[12]), "+f"(d[13]), "+f"(d[14]), "+f"(d[15]),
        "+f"(d[16]), "+f"(d[17]), "+f"(d[18]), "+f"(d[19]), "+f"(d[20]), "+f"(d[21]), "+f"(d[22]), "+f"(d[23]),
        "+f"(d[24]), "+f"(d[25]), "+f"(d[26]), "+f"(d[27]), "+f"(d[28]), "+f"(d[29]), "+f"(d[30]), "+f"(d[31]),
        "+f"(d[32]), "+f"(d[33]), "+f"(d[34]), "+f"(d[35]), "+f"(d[36]), "+f"(d[37]), "+f"(d[38]), "+f"(d[39]),
        "+f"(d[40]), "+f"(d[41]), "+f"(d[42]), "+f"(d[43]), "+f"(d[44]), "+f"(d[45]), "+f"(d[46]), "+f"(d[47]),
        "+f"(d[48]), "+f"(d[49]), "+f"(d[50]), "+f"(d[51]), "+f"(d[52]), "+f"(d[53]), "+f"(d[54]), "+f"(d[55]),
        "+f"(d[56]), "+f"(d[57]), "+f"(d[58]), "+f"(d[59]), "+f"(d[60]), "+f"(d[61]), "+f"(d[62]), "+f"(d[63])
      : "r"(a[0]), "r"(a[1]), "r"(a[2]), "r"(a[3]), "l"(db), "r"(accum));
}

__device__ __forceinline__ void wgmma_rs_n64(float (&d)[32], const uint32_t* a, uint64_t db, int accum) {
  asm volatile(
      "{\n.reg .pred p;\nsetp.ne.b32 p, %37, 0;\n"
      "wgmma.mma_async.sync.aligned.m64n64k16.f32.bf16.bf16 "
      "{%0,%1,%2,%3,%4,%5,%6,%7,%8,%9,%10,%11,%12,%13,%14,%15,%16,%17,%18,%19,%20,%21,%22,%23,%24,%25,%26,%27,%28,%29,%30,%31}, "
      "{%32,%33,%34,%35}, %36, p, 1, 1, 1;\n}\n"
      : "+f"(d[0]), "+f"(d[1]), "+f"(d[2]), "+f"(d[3]), "+f"(d[4]), "+f"(d[5]), "+f"(d[6]), "+f"(d[7]),
        "+f"(d[8]), "+f"(d[9]), "+f"(d[10]), "+f"(d[11]), "+f"(d[12]), "+f"(d[13]), "+f"(d[14]), "+f"(d[15]),
        "+f"(d[16]), "+f"(d[17]), "+f"(d[18]), "+f"(d[19]), "+f"(d[20]), "+f"(d[21]), "+f"(d[22]), "+f"(d[23]),
        "+f"(d[24]), "+f"(d[25]), "+f"(d[26]), "+f"(d[27]), "+f"(d[28]), "+f"(d[29]), "+f"(d[30]), "+f"(d[31])
      : "r"(a[0]), "r"(a[1]), "r"(a[2]), "r"(a[3]), "l"(db), "r"(accum));
}

struct SsmParams {
  const __nv_bfloat16 *x, *a_re, *a_im, *b_re, *b_im, *c_re, *c_im, *log_dt, *dskip, *w1, *w3, *w2;
};
struct C2 {
  float r, i;
};
__device__ __forceinline__ C2 cmul(C2 a, C2 b) { return {fmaf(a.r, b.r, -a.i * b.i), fmaf(a.r, b.i, a.i * b.r)}; }
__device__ __forceinline__ C2 cexp_pow(float a2, float rev, float l) {
  float m, t = rev * l, sn, cs;
  asm("ex2.approx.ftz.f32 %0, %1;" : "=f"(m) : "f"(a2 * l));
  t = (t - rintf(t)) * 6.283185307179586f;
  asm("sin.approx.ftz.f32 %0, %1;" : "=f"(sn) : "f"(t));
  asm("cos.approx.ftz.f32 %0, %1;" : "=f"(cs) : "f"(t));
  return {m * cs, m * sn};
}
__device__ __forceinline__ void store8(uint32_t addr, const C2* v, float isign) {
  uint32_t re[4], im[4];
#pragma unroll
  for (int i = 0; i < 4; i++) {
    re[i] = pack_bf16(v[2 * i].r, v[2 * i + 1].r);
    im[i] = pack_bf16(isign * v[2 * i].i, isign * v[2 * i + 1].i);
  }
  sts128(addr, re);
  sts128(addr + WS_WARP / 2, im);
}
struct ModeIn {
  float ar, ai, br, bi, cr, ci, ldt;
};
__device__ __forceinline__ ModeIn load_mode(const SsmParams& p, int d, int n) {
  const int i = d * NMODE + n;
  return {__bfloat162float(p.a_re[i]), __bfloat162float(p.a_im[i]), __bfloat162float(p.b_re[i]), __bfloat162float(p.b_im[i]),
          __bfloat162float(p.c_re[i]), __bfloat162float(p.c_im[i]), __bfloat162float(p.log_dt[d])};
}

__device__ __forceinline__ void kgen_task(uint32_t sb, int wg, const ModeIn in, int local) {
  const int t = threadIdx.x & 127, w = t >> 5, lane = t & 31;
  const uint32_t ws = sb + OFF_WS + wg * WS_BYTES, my = ws + w * WS_WARP, row = my + lane * 112;
  const float dt = round_bf16(__expf(in.ldt));
  const float a2 = dt * in.ar * 1.4426950408889634f, rev = dt * in.ai * 0.15915494309189535f;
  const C2 e1 = cexp_pow(a2, rev, 1.f), e8 = cexp_pow(a2, rev, 8.f), e256 = cexp_pow(a2, rev, 256.f);
  {
    C2 y[8];
    y[0] = {1.f, 0.f};
    y[1] = e8;
    y[2] = cmul(e8, e8);
    y[3] = cmul(y[2], e8);
    y[4] = cmul(y[2], y[2]);
    y[5] = cmul(y[4], y[1]);
    y[6] = cmul(y[4], y[2]);
    y[7] = cmul(y[4], y[3]);
    const C2 e64 = cmul(y[4], y[4]);
    store8(row, y, 1.f);
#pragma unroll
    for (int c = 1; c < 4; c++) {
#pragma unroll
      for (int i = 0; i < 8; i++) y[i] = (c == 1 && i == 0) ? e64 : cmul(y[i], e64);
      store8(row + 16 * c, y, 1.f);
    }
  }
  {
    C2 x[8], z[8];
    x[0] = cmul({in.cr, in.ci}, {dt * in.br, dt * in.bi});
    x[1] = cmul(x[0], e1);
    const C2 e2 = cmul(e1, e1);
#pragma unroll
    for (int i = 2; i < 8; i++) x[i] = cmul(x[i - 2], e2);
    store8(row + 64, x, -1.f);
#pragma unroll
    for (int i = 0; i < 4; i++) z[i] = cmul(x[2 * i], e256);
    z[4] = cmul(z[0], e256);
    z[5] = cmul(z[2], e256);
    z[6] = cmul(z[4], e256);
    z[7] = cmul(z[5], e256);
    store8(row + 80, z, -1.f);
    const C2 e512 = cmul(e256, e256);
    x[0] = cmul(z[4], e512);
    x[1] = cmul(z[6], e512);
    x[2] = cmul(x[0], e512);
    x[3] = cmul(x[1], e512);
    x[4] = cmul(x[2], e512);
    x[5] = x[6] = x[7] = {0.f, 0.f};
    store8(row + 96, x, -1.f);
  }
  __syncwarp();
  float acc[6][4];
#pragma unroll
  for (int i = 0; i < 6; i++) acc[i][0] = acc[i][1] = acc[i][2] = acc[i][3] = 0.f;
  const uint32_t aa = my + (lane >> 4) * (WS_WARP / 2) + (lane & 7) * 112 + ((lane >> 3) & 1) * 16;
  const uint32_t ba = my + ((lane >> 3) & 1) * (WS_WARP / 2) + (lane & 7) * 112 + (lane >> 4) * 16 + 64;
#pragma unroll
  for (int ks = 0; ks < 4; ks++) {
    uint32_t a[2][4], b[6];
    ldsm4t(a[0], aa + ks * 896);
    ldsm4t(a[1], aa + ks * 896 + 32);
    ldsm4t(b, ba + ks * 896);
    ldsm2t(b + 4, ba + ks * 896 + 32);
#pragma unroll
    for (int nt = 0; nt < 3; nt++)
#pragma unroll
      for (int mt = 0; mt < 2; mt++) mma_bf16(acc[nt * 2 + mt], a[mt][0], a[mt][1], a[mt][2], a[mt][3], &b[2 * nt]);
  }
  __syncwarp();
#pragma unroll
  for (int i = 0; i < 6; i++) sts128(my + i * 512 + lane * 16, reinterpret_cast<const uint32_t*>(acc[i]));
  wg_bar(wg);
  const uint32_t kc = ws + WS_KC;
  {
    const int q = (t >> 1) & 3, j = (t >> 6) * 16 + ((t >> 3) & 7) + (t & 1) * 8;
#pragma unroll
    for (int k = 0; k < 3; k++) {
      float v0 = 0.f, v1 = 0.f;
#pragma unroll
      for (int src = 0; src < 4; src++) {
        uint32_t v[2];
        lds64(v, ws + src * WS_WARP + k * 1024 + t * 8);
        v0 += __uint_as_float(v[0]);
        v1 += __uint_as_float(v[1]);
      }
      const uint32_t pk = pack_bf16(v0, v1);
      if (k == 0) {
        sts32(kc + 2 * (8 * j + 2 * q), pk);
      } else if (k == 1) {
        sts32(kc + 2 * (q < 2 ? 256 + 4 * j + 2 * q : 256 + 64 * q + 2 * j), pk);
      } else {
        if (q < 2 || (q == 2 && j == 0)) sts16(kc + 2 * (512 + 64 * q + j), pk);
        if (q < 2) sts16(kc + 2 * (544 + 64 * q + j), pk >> 16);
      }
    }
  }
  wg_bar(wg);
  const uint32_t pkb = sb + OFF_PK + local * PK_PITCH + 32 + t * 16;
  uint32_t o[4];
  if (t < 64) {
    uint32_t v[2];
    lds64(v, kc + 8 * t);
    const uint32_t prev = lds16(kc + 8 * t - 2);
    o[0] = __byte_perm(v[0], prev, 0x5410);
    o[1] = __byte_perm(v[0], 0, 0x1032);
    o[2] = __byte_perm(v[1], v[0], 0x7610);
    o[3] = __byte_perm(v[1], 0, 0x1032);
  } else {
    const uint32_t v = lds32(kc + 2 * (128 + 2 * t)), v2 = lds16(kc + 2 * (130 + 2 * t));
    const uint32_t prev = lds16(kc + 2 * (t == 64 ? 255 : 128 + 2 * t));
    o[0] = __byte_perm(v, prev, 0x5410);
    o[1] = __byte_perm(v, 0, 0x1010);
    o[2] = __byte_perm(v, 0, 0x1032);
    o[3] = __byte_perm(v2, v, 0x7610);
  }
  sts128(pkb, o);
  {
    const uint32_t v0 = lds16(kc + 2 * (384 + t)), v1 = lds16(kc + 2 * (385 + t)), vm = (t & 1) ? v1 : v0;
    o[0] = o[1] = __byte_perm(v0, 0, 0x1010);
    o[2] = __byte_perm(vm, v0, 0x5410);
    o[3] = __byte_perm(v1, vm, 0x5410);
    sts128(pkb + 2048, o);
  }
#pragma unroll
  for (int k = 0; k < 2; k++) {
    const int m = (t >> 1) + 64 * k;
    const uint32_t v0 = lds16(kc + 2 * (512 + m)), v1 = lds16(kc + 2 * (512 + m + (t & 1))), vm = (m & 1) ? v1 : v0;
    o[0] = __byte_perm(vm, v0, 0x5410);
    o[1] = __byte_perm(v1, vm, 0x5410);
    o[2] = o[3] = __byte_perm(v1, 0, 0x1010);
    sts128(pkb + 4096 + 2048 * k, o);
  }
}

template <int T0, int T1>
__device__ __forceinline__ void conv_task(uint32_t sb, int wg, int local, int d, uint32_t dsk) {
  constexpr int NT = T1 - T0, NB = (T1 + 1) & ~1;
  const int t = threadIdx.x & 127, w = t >> 5, lane = t & 31;
  float acc[NT][4];
#pragma unroll
  for (int i = 0; i < NT; i++) acc[i][0] = acc[i][1] = acc[i][2] = acc[i][3] = 0.f;
  const uint32_t ub = sb + OFF_U + local * U_PITCH + 128;
#pragma unroll 1
  for (int rho = 2 * w; rho < 2 * w + 2; rho++) {
    uint32_t b[NB][2];
    const uint32_t ua = ub + 16 * (lane - rho);
    const uint32_t pa = sb + OFF_PK + local * PK_PITCH + 32 + 4 * (8 * rho + (lane >> 2) - 2 * (lane & 3));
#pragma unroll
    for (int i = 0; i < NB; i += 2) ldsm4(b[i], ua + 256 * i);
    uint32_t cm = 0;
#pragma unroll
    for (int i = 0; i < T1; i++) {
      const uint32_t c0 = lds32(pa + 512 * i), cp = lds32(pa + 512 * i + 256);
#pragma unroll
      for (int tt = (i > T0 ? i : T0); tt < T1; tt++) mma_bf16(acc[tt - T0], c0, cp, cm, c0, b[tt - i]);
      cm = cp;
    }
  }
  const uint32_t ws = sb + OFF_WS + wg * WS_BYTES + lane * 16;
  wg_bar(wg);
#pragma unroll
  for (int i = 0; i < NT; i++) sts128(ws + (i * 4 + w) * 512, reinterpret_cast<const uint32_t*>(acc[i]));
  wg_bar(wg);
  uint32_t* hrow = reinterpret_cast<uint32_t*>(g_hT + d * L) + lane;
#pragma unroll
  for (int j = 0; j < (NT + 3) / 4; j++) {
    const int i = 4 * j + w;
    if (4 * j + 3 < NT || i < NT) {
      float y[4] = {0.f, 0.f, 0.f, 0.f};
#pragma unroll
      for (int src = 0; src < 4; src++) {
        uint32_t v[4];
        lds128(v, ws + (i * 4 + src) * 512);
#pragma unroll
        for (int e = 0; e < 4; e++) y[e] += __uint_as_float(v[e]);
      }
#pragma unroll
      for (int h = 0; h < 2; h++) {
        uint32_t yy;
        asm volatile("movmatrix.sync.aligned.m8n8.trans.b16 %0, %1;" : "=r"(yy) : "r"(pack_bf16(y[2 * h], y[2 * h + 1])));
        const int seg = 2 * (T0 + i) + h;
        const uint32_t u = lds32(ub + seg * 128 + lane * 4);
        const uint32_t x = lds32(sb + OFF_X + local * X_PITCH + seg * 128 + lane * 4);
        hrow[seg * 32] = add_bf16x2(x, add_bf16x2(yy, mul_bf16x2(u, dsk)));
      }
    }
  }
}

__device__ __forceinline__ uint32_t nz_bf16(float v) {
  const uint32_t b = pack_bf16(v, 0.f);
  return b ? b : 0x8000u;
}

__device__ __forceinline__ void ln1_stats(uint32_t sb, int c, const uint4 (&xv)[9]) {
  const int t = threadIdx.x & 127;
  float s = 0.f, q = 0.f;
#pragma unroll
  for (int i = 0; i < 9; i++) {
    const uint32_t v[4] = {xv[i].x, xv[i].y, xv[i].z, xv[i].w};
#pragma unroll
    for (int e = 0; e < 4; e++) {
      const float lo = bf_lo(v[e]), hi = bf_hi(v[e]);
      s += lo + hi;
      q = fmaf(lo, lo, fmaf(hi, hi, q));
    }
  }
#pragma unroll
  for (int o = 1; o < 8; o <<= 1) {
    s += __shfl_xor_sync(~0u, s, o);
    q += __shfl_xor_sync(~0u, q, o);
  }
  const float m = s * (1.f / D), r = ln_rstd(fmaxf(q * (1.f / D) - m * m, 0.f));
  const int row = t >> 3, sub = t & 7;
  const float val = sub == 0 ? m : sub == 1 ? r : r - round_bf16(r);
  if (sub < 3) sts16(sb + OFF_MISC + (row >> 3) * 48 + sub * 16 + (row & 7) * 2, nz_bf16(val));
  wg_bar(2);
  if (t < 6) {
    uint32_t v[4];
    lds128(v, sb + OFF_MISC + t * 16);
    asm volatile("st.relaxed.gpu.global.v4.b32 [%0], {%1,%2,%3,%4};" ::"l"(&g_stats[c * 6 + t]), "r"(v[0]), "r"(v[1]),
                 "r"(v[2]), "r"(v[3]) : "memory");
  }
}

__device__ __forceinline__ void ln1_apply(uint32_t sb, int c) {
  const int t = threadIdx.x & 127, w = t >> 5, lane = t & 31, rank = c & 1, q = lane & 3;
  uint32_t dst[2], dst2 = 0;
  bool ok[2], both[2];
#pragma unroll
  for (int hf = 0; hf < 2; hf++) {
    const int rel = 8 * hf + (lane >> 2) - ((c >> 1) & 7);
    ok[hf] = rel >= 0 && rel < 9;
    both[hf] = rel == 4;
    dst[hf] = mapa(sb, rel > 4) + (rel > 4 ? rel - 5 : rel) * 64;
  }
  dst2 = mapa(sb, 1) + 4 * 64;
  const uint32_t pos = 2 * (1024 * rank + 8 * q);
#pragma unroll 1
  for (int it = 0; it < 2; it++) {
    uint32_t st[4][12];
    const uint4* sp = &g_stats[(128 * rank + 64 * it + 4 * w + q) * 3];
    uint32_t spins = 0;
    while (true) {
      uint32_t mn = ~0u;
#pragma unroll
      for (int k = 0; k < 4; k++)
#pragma unroll
        for (int e = 0; e < 3; e++) {
          uint32_t* v = &st[k][4 * e];
          asm volatile("ld.relaxed.gpu.global.v4.b32 {%0,%1,%2,%3}, [%4];"
                       : "=r"(v[0]), "=r"(v[1]), "=r"(v[2]), "=r"(v[3]) : "l"(sp + k * 48 + e) : "memory");
        }
#pragma unroll
      for (int k = 0; k < 4; k++)
#pragma unroll
        for (int e = 0; e < 12; e++) mn = min(mn, st[k][e]);
      if (__all_sync(~0u, mn != 0)) break;
      if (++spins > SPIN_LIMIT) __trap();
    }
    if (it == 0) STAMPC(t == 0, 17);
#pragma unroll
    for (int k = 0; k < 4; k++) {
      const int grp = 16 * it + 4 * k + w;
      if ((k & 1) == 0) mbar_wait(sb + B_G + 8 * (2 * it + (k >> 1)), 0);
#pragma unroll
      for (int hf = 0; hf < 2; hf++) {
        uint32_t x[4], u[4];
        ldsm4t(x, sb + OFF_G + grp * 1024 + lane * 32 + ((hf ^ ((lane >> 2) & 1)) << 4));
#pragma unroll
        for (int e = 0; e < 4; e++) {
          const uint32_t dv = sub_bf16x2(x[e], st[k][e]);
          u[e] = fma_bf16x2(dv, st[k][4 + e], mul_bf16x2(dv, st[k][8 + e]));
        }
        const uint32_t base = dst[hf] & ~1023u, loc = (dst[hf] & 1023u) >> 6, off = pos + grp * 64;
        if (ok[hf]) {
          st_async128(base + OFF_U + loc * U_PITCH + 128 + off, u, base + B_UX);
          st_async128(base + OFF_X + loc * X_PITCH + off, x, base + B_UX);
        }
        if (both[hf]) {
          const uint32_t b2 = dst2 & ~1023u;
          st_async128(b2 + OFF_U + 4 * U_PITCH + 128 + off, u, b2 + B_UX);
          st_async128(b2 + OFF_X + 4 * X_PITCH + off, x, b2 + B_UX);
        }
      }
    }
  }
}

struct Ring {
  uint32_t slot, phase;
  __device__ __forceinline__ void next() {
    if (++slot == NS) { slot = 0; phase ^= 1; }
  }
};

__device__ __forceinline__ uint64_t bdesc(uint32_t addr) {
  return (uint64_t)((addr & 0x3FFFF) >> 4) | ((uint64_t)(BOX >> 4) << 16) | ((uint64_t)(1024 >> 4) << 32) | (1ull << 62);
}
__device__ __forceinline__ void release_slot(uint32_t sb, uint32_t slot, int lane) {
  if (lane == 0) mbar_arrive(sb + B_EMPTY + 8 * slot);
}
__device__ __forceinline__ void add_partial(float* sum, uint32_t addr) {
#pragma unroll
  for (int j = 0; j < 4; j++) {
    uint32_t v[4];
    lds128(v, addr + j * 512);
#pragma unroll
    for (int i = 0; i < 4; i++) {
      sum[8 * j + 2 * i] += bf_lo(v[i]);
      sum[8 * j + 2 * i + 1] += bf_hi(v[i]);
      asm volatile("" : "+f"(sum[8 * j + 2 * i]), "+f"(sum[8 * j + 2 * i + 1]));
    }
  }
}
__device__ __forceinline__ void stage_partial(const float* acc, uint32_t addr, uint32_t bar, int lane) {
#pragma unroll
  for (int j = 0; j < 4; j++) {
    uint32_t p[4];
#pragma unroll
    for (int i = 0; i < 4; i++) p[i] = pack_bf16(acc[8 * j + 2 * i], acc[8 * j + 2 * i + 1]);
    sts128(addr + j * 512, p);
  }
  asm volatile("fence.proxy.async.shared::cta;" ::: "memory");
  __syncwarp();
  if (lane == 0) mbar_arrive(bar);
}
__device__ __forceinline__ void send_partial(const float* acc, uint32_t addr, uint32_t bar) {
#pragma unroll
  for (int j = 0; j < 4; j++) {
    uint32_t p[4];
#pragma unroll
    for (int i = 0; i < 4; i++) p[i] = pack_bf16(acc[8 * j + 2 * i], acc[8 * j + 2 * i + 1]);
    st_async128(addr + j * 512, p, bar);
  }
}
__device__ __forceinline__ void lag_sync(int wg) {
  if (wg == 1) asm volatile("bar.sync 4, 256;" ::: "memory");
}
__device__ __forceinline__ void lag_arrive(int wg) {
  if (wg == 0) asm volatile("bar.arrive 4, 256;" ::: "memory");
}

template <int T, typename Fn>
__device__ __forceinline__ void step64(float (&acc)[32], const uint32_t (&A)[144], uint32_t sb, uint64_t desc0, Ring& ring,
                                       int wg, int lane, Fn&& side) {
  uint32_t prev = 0;
#pragma unroll
  for (int st = 0; st < 5; st++) {
    mbar_wait(sb + B_FULL + 8 * ring.slot, ring.phase);
    const uint64_t db = desc0 + ring.slot * (SLOT >> 4);
    if (st == 5 - LAG3) lag_sync(wg);
    WG_FENCE();
#pragma unroll
    for (int k = 0; k < (st < 4 ? 8 : 4); k++) wgmma_rs_n64(acc, &A[(st * 8 + k) * 4], db + k * 128, st + k);
    WG_COMMIT();
    if (st == 4) lag_arrive(wg);
    if (st > 0 && T * 5 + st - 1 < 15 - NS) {
      WG_WAIT(1);
      release_slot(sb, prev, lane);
    }
    prev = ring.slot;
    ring.next();
    side(st);
  }
  WG_WAIT(0);
  if (T * 5 + 4 < 15 - NS) release_slot(sb, prev, lane);
}

__device__ __forceinline__ void ffn_consumer(uint32_t sb, int r, int s, __nv_bfloat16* __restrict__ out) {
  const int tid = threadIdx.x, wg = tid >> 7, w = (tid >> 5) & 3, lane = tid & 31;
  const uint32_t stash = OFF_STASH + wg * 8 * BOX;
  const uint32_t priv = sb + stash + w * 2048 + lane * 16;
  uint32_t A[144];
  float rs0, rs1;
  const uint32_t tr_off = ((lane >> 4) * 8 + (lane & 7)) * 128 + (((2 * w + ((lane >> 3) & 1)) ^ (lane & 7)) << 4);
  {
    float s0 = 0.f, s1 = 0.f, q0 = 0.f, q1 = 0.f;
#pragma unroll
    for (int kb = 0; kb < 9; kb++) {
      if (kb % 3 == 0) mbar_wait(sb + B_H + 8 * (wg * 3 + kb / 3), 0);
      const uint32_t box = sb + (kb < 8 ? stash + kb * BOX : (NS - 1) * SLOT + wg * BOX) + tr_off;
#pragma unroll
      for (int k = 0; k < 4; k++) {
        uint32_t* a = &A[(kb * 4 + k) * 4];
        ldsm4t(a, box + k * 2048);
#pragma unroll
        for (int i = 0; i < 4; i++) {
          const float lo = bf_lo(a[i]), hi = bf_hi(a[i]);
          if (i & 1) { s1 += lo + hi; q1 = fmaf(lo, lo, fmaf(hi, hi, q1)); }
          else { s0 += lo + hi; q0 = fmaf(lo, lo, fmaf(hi, hi, q0)); }
        }
      }
      asm volatile("" : "+f"(s0), "+f"(s1), "+f"(q0), "+f"(q1));
      if (kb == 0) STAMP(24 + wg);
      if (kb == 8) STAMP(26 + wg);
    }
    release_slot(sb, NS - 1, lane);
#pragma unroll
    for (int o = 1; o <= 2; o <<= 1) {
      s0 += __shfl_xor_sync(~0u, s0, o); s1 += __shfl_xor_sync(~0u, s1, o);
      q0 += __shfl_xor_sync(~0u, q0, o); q1 += __shfl_xor_sync(~0u, q1, o);
    }
    const float m0 = s0 * (1.f / D), m1 = s1 * (1.f / D);
    rs0 = ln_rstd(fmaxf(q0 * (1.f / D) - m0 * m0, 0.f));
    rs1 = ln_rstd(fmaxf(q1 * (1.f / D) - m1 * m1, 0.f));
    const uint32_t mm0 = pack_bf16(m0, m0), mm1 = pack_bf16(m1, m1);
#pragma unroll
    for (int i = 0; i < 144; i++) A[i] = sub_bf16x2(A[i], (i & 1) ? mm1 : mm0);
    wg_bar(wg);
  }
  STAMP(2 + wg);

  Ring ring{0, 0};
  const uint64_t desc0 = bdesc(sb);
  const uint32_t peer = mapa(sb, (s & 1) ^ 1) - sb;
#pragma unroll 1
  for (int step = 0; step < 12; step++) {
    float acc[64];
    uint32_t prev = 0;
#pragma unroll
    for (int kb = 0; kb < 9; kb++) {
      mbar_wait(sb + B_FULL + 8 * ring.slot, ring.phase);
      const uint64_t db = desc0 + ring.slot * (SLOT >> 4);
      if (LAG1 == LAG2) {
        if (kb == 9 - LAG1) lag_sync(wg);
      } else {
        if (kb == 9 - LAG1 && step < 9) lag_sync(wg);
        if (kb == 9 - LAG2 && step >= 9) lag_sync(wg);
      }
      WG_FENCE();
#pragma unroll
      for (int k = 0; k < 4; k++) wgmma_rs_n128(acc, &A[(kb * 4 + k) * 4], db + k * 128, kb + k);
      WG_COMMIT();
      if (kb == 8) lag_arrive(wg);
      if (kb > 0) {
        WG_WAIT(1);
        release_slot(sb, prev, lane);
      }
      prev = ring.slot;
      ring.next();
    }
    WG_WAIT(0);
    release_slot(sb, prev, lane);
    if (step < 9) {
      uint32_t hp[16];
      const float c0 = 0.5f * rs0, c1 = 0.5f * rs1;
#pragma unroll
      for (int i = 0; i < 16; i++) {
        const float c = (i & 1) ? c1 : c0, rr = (i & 1) ? rs1 : rs0;
        const float g0 = acc[2 * i] * c, g1 = acc[2 * i + 1] * c;
        const float h0 = fmaf(g0, tanh_hw(g0), g0) * (acc[32 + 2 * i] * rr);
        const float h1 = fmaf(g1, tanh_hw(g1), g1) * (acc[33 + 2 * i] * rr);
        hp[i] = pack_bf16(h0, h1);
      }
      if (step < 8) {
#pragma unroll
        for (int j = 0; j < 4; j++) sts128(priv + step * BOX + j * 512, &hp[4 * j]);
      } else {
#pragma unroll
        for (int i = 0; i < 16; i++) A[128 + i] = hp[i];
#pragma unroll
        for (int c = 0; c < 8; c++)
#pragma unroll
          for (int j = 0; j < 4; j++) lds128(&A[16 * c + 4 * j], priv + c * BOX + j * 512);
        __syncwarp();
        if (lane == 0) mbar_arrive_cluster(sb + peer + B_PRDY + 8 * wg);
        STAMP(4 + wg);
      }
    } else {
      const int e = step - 9;
      if (e == 0) {
        mbar_wait(sb + B_PRDY + 8 * wg, 0);
      } else {
        mbar_wait(sb + B_XIN + 8 * (wg * 4 + e - 1), 0);
        add_partial(acc + 32, priv + ((e - 1) & 1) * BOX);
        if (e == 2) mbar_wait(sb + B_SE + 8 * (wg * 2), 0);
      }
      stage_partial(acc + 32, priv + (2 + (e & 1)) * BOX, sb + B_SF + 8 * (wg * 4 + e), lane);
      send_partial(acc, priv + peer + (e & 1) * BOX, sb + peer + B_XIN + 8 * (wg * 4 + e));
    }
  }
  STAMP(6 + wg);

  float acc[32];
  {
    uint2 p8[8];
    uint32_t res[4];
    const int col = 512 + 16 * (tid >> 6) + 8 * (tid & 1) + 2 * ((tid >> 1) & 3), row = r * 128 + s * 16 + ((tid >> 3) & 7);
    step64<0>(acc, A, sb, desc0, ring, wg, lane, [&](int st) {
      if (st == 0) {
        mbar_wait(sb + B_B8, 0);
        const uint2* src = reinterpret_cast<const uint2*>(&g_part8[r * 8 * 1024 + s * 128]) + tid;
#pragma unroll
        for (int i = 0; i < 8; i++) p8[i] = __ldcg(src + i * 2048);
        const unsigned short* hp = reinterpret_cast<const unsigned short*>(g_hT) + col * L + row;
#pragma unroll
        for (int i = 0; i < 4; i++) res[i] = __ldcg(hp + (i & 1) * L + (i >> 1) * 8);
      } else if (st == 4) {
        float v[4];
#pragma unroll
        for (int i = 0; i < 4; i++) v[i] = bf_lo(res[i]);
#pragma unroll
        for (int i = 0; i < 8; i++) {
          v[0] += bf_lo(p8[i].x); v[1] += bf_hi(p8[i].x);
          v[2] += bf_lo(p8[i].y); v[3] += bf_hi(p8[i].y);
        }
        *reinterpret_cast<uint32_t*>(out + row * D + col) = pack_bf16(v[0], v[1]);
        *reinterpret_cast<uint32_t*>(out + (row + 8) * D + col) = pack_bf16(v[2], v[3]);
      }
    });
    mbar_wait(sb + B_XIN + 8 * (wg * 4 + 2), 0);
    add_partial(acc, priv);
    mbar_wait(sb + B_SE + 8 * (wg * 2 + 1), 0);
    stage_partial(acc, priv + 3 * BOX, sb + B_SF + 8 * (wg * 4 + 3), lane);
  }
  STAMPC(tid == 0, 12);
  float sum[32];
  step64<1>(acc, A, sb, desc0, ring, wg, lane, [&](int st) {
    if (st == 1) {
      mbar_wait(sb + B_LIN + 8 * (wg * 2), 0);
#pragma unroll
      for (int k = 0; k < 4; k++) {
        uint32_t v[4];
        ldsm4t(v, sb + stash + 7 * BOX + tr_off + k * 2048);
#pragma unroll
        for (int i = 0; i < 4; i++) {
          sum[8 * k + 2 * i] = bf_lo(v[i]);
          sum[8 * k + 2 * i + 1] = bf_hi(v[i]);
        }
      }
      add_partial(sum, priv + 4 * BOX);
    }
  });
  send_partial(acc, priv + peer + BOX, sb + peer + B_XIN + 8 * (wg * 4 + 3));
  STAMPC(tid == 0, 13);
  step64<2>(acc, A, sb, desc0, ring, wg, lane, [&](int st) {
    if (st == 4) {
      mbar_wait(sb + B_LIN + 8 * (wg * 2 + 1), 0);
      add_partial(sum, priv + 5 * BOX);
      add_partial(sum, priv + 6 * BOX);
      mbar_wait(sb + B_XIN + 8 * (wg * 4 + 3), 0);
      add_partial(sum, priv + BOX);
    }
  });
  STAMP(8 + wg);
  const uint32_t ob = sb + stash + 4 * BOX + w * 2048;
  __syncwarp();
#pragma unroll
  for (int i = 0; i < 4; i++) {
    uint32_t p[4];
#pragma unroll
    for (int j = 0; j < 4; j++)
      p[j] = pack_bf16(acc[8 * i + 2 * j] + sum[8 * i + 2 * j], acc[8 * i + 2 * j + 1] + sum[8 * i + 2 * j + 1]);
    stsm4(ob + (lane & 15) * 128 + (((2 * i + (lane >> 4)) ^ (lane & 7)) << 4), p);
  }
  __syncwarp();
  __nv_bfloat16* o = out + (r * 128 + wg * 64 + w * 16 + (lane >> 3)) * D + s * 64 + (lane & 7) * 8;
#pragma unroll
  for (int i = 0; i < 4; i++) {
    const int row = 4 * i + (lane >> 3);
    uint32_t v[4];
    lds128(v, ob + row * 128 + (((lane & 7) ^ (row & 7)) << 4));
    *reinterpret_cast<uint4*>(o + 4 * i * D) = make_uint4(v[0], v[1], v[2], v[3]);
  }
  STAMP(10 + wg);
}

__device__ __forceinline__ void load_stage(uint32_t sb, uint32_t slot, int it, int s, const CUtensorMap* w1,
                                           const CUtensorMap* w3, const CUtensorMap* w2) {
  const uint32_t bar = sb + B_FULL + 8 * slot, dst = sb + slot * SLOT;
  if (it < 81) {
    const int step = it / 9, kb = it - step * 9;
    mbar_expect(bar, SLOT);
    tma2d(dst, w1, s * 576 + step * 64, kb * 64, bar);
    tma2d(dst + BOX, w3, s * 576 + step * 64, kb * 64, bar);
  } else if (it < 108) {
    const int e = (it - 81) / 9, kb = it - 81 - e * 9;
    mbar_expect(bar, SLOT);
    tma2d(dst, w2, (((s + 2 * e + 2) & 7) ^ 1) * 64, s * 576 + kb * 64, bar);
    tma2d(dst + BOX, w2, (e == 0 ? 8 : (s + 2 * e) & 7) * 64, s * 576 + kb * 64, bar);
  } else {
    const int e = (it - 108) / 5, st = it - 108 - e * 5;
    const int blk = e == 0 ? (s + 6) & 7 : e == 1 ? s ^ 1 : s;
    mbar_expect(bar, st < 4 ? SLOT : BOX);
    tma2d(dst, w2, blk * 64, s * 576 + st * 128, bar);
    if (st < 4) tma2d(dst + BOX, w2, blk * 64, s * 576 + st * 128 + 64, bar);
  }
}

__device__ __forceinline__ void ffn_producer(uint32_t sb, int s, int first, const CUtensorMap* w1, const CUtensorMap* w3,
                                             const CUtensorMap* w2) {
  Ring ring{(uint32_t)first, 1};
#pragma unroll 1
  for (int it = first; it < 123; it++) {
    mbar_wait(sb + B_EMPTY + 8 * ring.slot, ring.slot == NS - 1 ? ring.phase ^ 1 : ring.phase);
    if (elect_one()) load_stage(sb, ring.slot, it, s, w1, w3, w2);
    __syncwarp();
    ring.next();
  }
}

__device__ __forceinline__ void ffn_sender(uint32_t sb, int r, int s, int wg) {
  const uint32_t stash = sb + OFF_STASH + wg * 8 * BOX;
#pragma unroll 1
  for (int e = 0; e < 4; e++) {
    mbar_wait(sb + B_SF + 8 * (wg * 4 + e), 0);
    if (elect_one()) {
      const int idx = ((r * 8 + ((s + 2 * e) & 7)) * 3 + e - 1) * 2 + wg;
      uint4* dst = e == 0 ? &g_part8[((r * 8 + s) * 2 + wg) * 512] : &g_part[idx * 512];
      const uint32_t src = stash + (2 + (e & 1)) * BOX;
#pragma unroll 1
      for (int q = 0; q < BOX / PACE; q++) {
        bulk_store(dst + q * (PACE / 16), src + q * PACE, PACE);
        asm volatile("cp.async.bulk.commit_group;" ::: "memory");
        asm volatile("cp.async.bulk.wait_group.read 0;" ::: "memory");
      }
      if (e < 2) mbar_arrive(sb + B_SE + 8 * (wg * 2 + e));
      asm volatile("cp.async.bulk.wait_group 0;" ::: "memory");
      asm volatile("fence.acq_rel.gpu;" ::: "memory");
      if (e > 0) {
        red_add(&g_flag[idx], 1);
      } else {
#pragma unroll
        for (int q = 0; q < 4; q++) red_add(&g_flag8[r * 8 + wg * 4 + q], 1);
      }
      STAMPC(e == 3, 28 + wg);
    }
    __syncwarp();
  }
}

__device__ __forceinline__ void ffn_receiver(uint32_t sb, int c, int r, int s, unsigned target, const CUtensorMap* ht) {
  const int lane = threadIdx.x & 31;
  wait_flag(&g_epoch, target);
  asm volatile("fence.proxy.async.global;" ::: "memory");
  STAMPC(lane == 0, 23);
  if (elect_one()) {
#pragma unroll
    for (int i = 0; i < 18; i++) {
      const int g = i / 9, kb = i % 9;
      const uint32_t dst = sb + (kb < 8 ? OFF_STASH + (g * 8 + kb) * BOX : (NS - 1) * SLOT + g * BOX);
      tma2d(dst, ht, r * 128 + g * 64, kb * 64, sb + B_H + 8 * (i / 3));
    }
  }
  __syncwarp();
  if (lane < 6) g_stats[c * 6 + lane] = make_uint4(0, 0, 0, 0);
#pragma unroll 1
  for (int wg = 0; wg < 2; wg++) {
    mbar_wait(sb + B_SF + 8 * (wg * 4), 0);
    if (elect_one()) tma2d(sb + OFF_STASH + (wg * 8 + 7) * BOX, ht, r * 128 + wg * 64, s * 64, sb + B_LIN + 8 * (wg * 2));
    __syncwarp();
  }
  wait_flag(&g_flag8[r * 8 + s], 8);
  __syncwarp();
  if (lane == 0) {
    g_flag8[r * 8 + s] = 0;
    mbar_arrive(sb + B_B8);
  }
#pragma unroll 1
  for (int i = 0; i < 6; i++) {
    const int idx = (r * 8 + s) * 6 + i, wg = i & 1;
    wait_flag(&g_flag[idx], 1);
    asm volatile("fence.proxy.async.global;" ::: "memory");
    __syncwarp();
    if (elect_one()) {
      g_flag[idx] = 0;
      bulk_load(sb + OFF_STASH + (wg * 8 + 4 + (i >> 1)) * BOX, &g_part[idx * 512], BOX, sb + B_LIN + 8 * (wg * 2 + (i > 1)));
    }
    __syncwarp();
  }
  STAMPC(lane == 0, 30);
}

__global__ void __launch_bounds__(384, 1)
fused_kernel(const __grid_constant__ CUtensorMap tm_w1, const __grid_constant__ CUtensorMap tm_w3,
             const __grid_constant__ CUtensorMap tm_w2, const __grid_constant__ CUtensorMap tm_ht,
             const __grid_constant__ CUtensorMap tm_x, const __grid_constant__ SsmParams p,
             __nv_bfloat16* __restrict__ out) {
  extern __shared__ __align__(1024) uint8_t smem[];
  uint32_t sb = (uint32_t)__cvta_generic_to_shared(smem);
  asm volatile("" : "+r"(sb));
  const int c = blockIdx.x, cl = c >> 1, rank = c & 1, tid = threadIdx.x, wg = tid >> 7;
  const int s = ((cl & 1) * 2 + ((cl >> 3) & 1)) * 2 + rank, r = ((cl >> 1) & 3) * 4 + (cl >> 4);
  STAMPC(tid == 0, 0);
  if (tid == 0) {
    if (sb & 1023) __trap();
    for (int i = 0; i < 4; i++) mbar_init(sb + B_G + 8 * i, 1);
    asm volatile("fence.mbarrier_init.release.cluster;" ::: "memory");
    for (int i = 0; i < 4; i++) {
      mbar_expect(sb + B_G + 8 * i, BOX);
      asm volatile(
          "cp.async.bulk.tensor.5d.shared::cluster.global.mbarrier::complete_tx::bytes [%0], [%1, {%3, %4, %4, %4, %5}], [%2];"
          ::"r"(sb + OFF_G + i * BOX), "l"(&tm_x), "r"(sb + B_G + 8 * i), "r"((9 * cl) & ~7), "r"(0), "r"(32 * rank + 8 * i)
          : "memory");
    }
  }
  if (tid == 32) {
    for (int i = 0; i < NS; i++) {
      mbar_init(sb + B_FULL + 8 * i, 1);
      mbar_init(sb + B_EMPTY + 8 * i, 8);
    }
    for (int i = 0; i < 6; i++) {
      mbar_init(sb + B_H + 8 * i, 1);
      mbar_expect(sb + B_H + 8 * i, 3 * BOX);
    }
    for (int i = 0; i < 8; i++) {
      mbar_init(sb + B_SF + 8 * i, 4);
      mbar_init(sb + B_XIN + 8 * i, 1);
      mbar_expect(sb + B_XIN + 8 * i, BOX);
    }
    for (int i = 0; i < 4; i++) {
      mbar_init(sb + B_SE + 8 * i, 1);
      mbar_init(sb + B_LIN + 8 * i, 1);
      mbar_expect(sb + B_LIN + 8 * i, 2 * BOX);
    }
    mbar_init(sb + B_PRDY, 4);
    mbar_init(sb + B_PRDY + 8, 4);
    mbar_init(sb + B_B8, 1);
    mbar_init(sb + B_UX, 1);
    mbar_expect(sb + B_UX, 5 * L * 4);
    asm volatile("fence.mbarrier_init.release.cluster;" ::: "memory");
  }
  unsigned target = 0;
  int first = 0;
  const int ch0 = 9 * cl + 5 * rank, chs = 9 * cl + 4;
  uint4 xv[9];
  if (wg == 2) {
    const uint4* xr = reinterpret_cast<const uint4*>(p.x + (16 * c + ((tid & 127) >> 3)) * D) + (tid & 7);
#pragma unroll
    for (int i = 0; i < 9; i++) xv[i] = __ldg(xr + 8 * i);
  }
  const ModeIn in0 = load_mode(p, ch0 + wg, tid & 127);
  const ModeIn in1 = load_mode(p, wg == 0 ? ch0 + 3 : chs, tid & 127);
  const int dA = wg == 1 ? ch0 + 3 : ch0 + wg, dB = wg == 0 ? ch0 + 3 : wg == 1 ? ch0 + 1 : chs;
  const uint32_t dskA = reinterpret_cast<const unsigned short*>(p.dskip)[dA] * 0x10001u;
  const uint32_t dskB = reinterpret_cast<const unsigned short*>(p.dskip)[dB] * 0x10001u;
  target = (*(volatile unsigned*)&g_epoch & ~511u) + 512;
  if (tid >= 64 && tid < 64 + 53) {
    const int i = tid - 64;
    const uint32_t z[4] = {0, 0, 0, 0};
    sts128(sb + (i < 40 ? OFF_U + (i >> 3) * U_PITCH + (i & 7) * 16
                        : i < 50 ? OFF_PK + ((i - 40) >> 1) * PK_PITCH + (i & 1) * 16
                                 : OFF_WS + (i - 50) * WS_BYTES + 4 * WS_WARP), z);
  }
  __syncthreads();
  asm volatile("barrier.cluster.arrive.relaxed.aligned;" ::: "memory");
  STAMPC(tid == 0, 1);
  if (wg == 2) ln1_stats(sb, c, xv);
  STAMPC(tid == 256, 14);
  kgen_task(sb, wg, in0, wg);
  STAMPC(tid == 0, 15);
  asm volatile("barrier.cluster.wait.aligned;" ::: "memory");
  if (wg < 2) {
    kgen_task(sb, wg, in1, 3 + wg);
    STAMPC(tid == 0, 16);
  } else {
    ln1_apply(sb, c);
    asm volatile("fence.proxy.async.shared::cta;" ::: "memory");
    wg_bar(2);
    STAMPC(tid == 256, 18);
    if (tid == 256) {
      load_stage(sb, 0, 0, s, &tm_w1, &tm_w3, &tm_w2);
      load_stage(sb, 1, 1, s, &tm_w1, &tm_w3, &tm_w2);
    }
    if (tid >= 288 && tid < 288 + 9) {
      const int i = tid - 288;
      const __nv_bfloat16* wp = (i < 3 ? p.w1 : i < 6 ? p.w3 : p.w2) + c * 20736 + (i % 3) * 6912;
      asm volatile("cp.async.bulk.prefetch.L2.global [%0], %1;" ::"l"(wp), "r"(13824) : "memory");
    }
  }
  first = 2;
  __syncthreads();
  mbar_wait(sb + B_UX, 0);
  STAMPC(tid == 0, 19);
  if (wg == 1) {
    conv_task<11, 16>(sb, wg, 3, dA, dskA);
    conv_task<0, 16>(sb, wg, 1, dB, dskB);
  } else {
    conv_task<0, 16>(sb, wg, wg, dA, dskA);
    if (wg == 2 && rank == 1) conv_task<11, 16>(sb, wg, 4, dB, dskB);
    else conv_task<0, 11>(sb, wg, 3 + (wg >> 1), dB, dskB);
  }
  STAMP(20 + wg);
  asm volatile("fence.proxy.async.shared::cta;" ::: "memory");
  wg_bar(wg);
  if ((tid & 127) == 64) {
    asm volatile("fence.acq_rel.gpu;" ::: "memory");
    red_add(&g_epoch, wg == 2 ? 2 : 1);
  }
  __syncthreads();

  if (tid < 256) {
    asm volatile("setmaxnreg.inc.sync.aligned.u32 240;");
    ffn_consumer(sb, r, s, out);
  } else {
    asm volatile("setmaxnreg.dec.sync.aligned.u32 24;");
    const int w = (tid >> 5) & 3;
    if (w == 0) ffn_producer(sb, s, first, &tm_w1, &tm_w3, &tm_w2);
    else if (w < 3) ffn_sender(sb, r, s, w - 1);
    else ffn_receiver(sb, c, r, s, target, &tm_ht);
  }
}

typedef CUresult (*EncodeFn)(CUtensorMap*, CUtensorMapDataType, cuuint32_t, void*, const cuuint64_t*, const cuuint64_t*,
                             const cuuint32_t*, const cuuint32_t*, CUtensorMapInterleave, CUtensorMapSwizzle,
                             CUtensorMapL2promotion, CUtensorMapFloatOOBfill);

void make_map(EncodeFn enc, CUtensorMap* m, void* p, uint64_t cols, uint64_t rows) {
  cuuint64_t dims[2] = {cols, rows}, strides[1] = {cols * 2};
  cuuint32_t box[2] = {64, 64}, es[2] = {1, 1};
  enc(m, CU_TENSOR_MAP_DATA_TYPE_BFLOAT16, 2, p, dims, strides, box, es, CU_TENSOR_MAP_INTERLEAVE_NONE,
      CU_TENSOR_MAP_SWIZZLE_128B, CU_TENSOR_MAP_L2_PROMOTION_L2_128B, CU_TENSOR_MAP_FLOAT_OOB_FILL_NONE);
}

}

extern "C" void kernel_launch(void* const* d_in, const int* in_sizes, int n_in, void* d_out, int out_size) {
  typedef const __nv_bfloat16* P;
  void* fn = nullptr;
  cudaDriverEntryPointQueryResult qr;
  cudaGetDriverEntryPoint("cuTensorMapEncodeTiled", &fn, cudaEnableDefault, &qr);
  EncodeFn enc = (EncodeFn)fn;
  void* hT = nullptr;
  cudaGetSymbolAddress(&hT, g_hT);
  CUtensorMap m1, m3, m2, mh, mx;
  make_map(enc, &m1, d_in[10], F, D);
  make_map(enc, &m3, d_in[11], F, D);
  make_map(enc, &m2, d_in[12], D, F);
  make_map(enc, &mh, hT, L, D);
  {
    cuuint64_t dims[5] = {D, 2, 4, 4, 64}, strides[4] = {D * 2, D * 16, D * 4, D * 64};
    cuuint32_t box[5] = {16, 2, 4, 4, 8}, es[5] = {1, 1, 1, 1, 1};
    enc(&mx, CU_TENSOR_MAP_DATA_TYPE_BFLOAT16, 5, d_in[0], dims, strides, box, es, CU_TENSOR_MAP_INTERLEAVE_NONE,
        CU_TENSOR_MAP_SWIZZLE_32B, CU_TENSOR_MAP_L2_PROMOTION_L2_128B, CU_TENSOR_MAP_FLOAT_OOB_FILL_NONE);
  }
  SsmParams p = {(P)d_in[0], (P)d_in[1], (P)d_in[2], (P)d_in[3], (P)d_in[4], (P)d_in[5],
                 (P)d_in[6], (P)d_in[7], (P)d_in[8], (P)d_in[10], (P)d_in[11], (P)d_in[12]};
  cudaFuncSetAttribute(fused_kernel, cudaFuncAttributeMaxDynamicSharedMemorySize, SMEM_BYTES);
  cudaLaunchConfig_t cfg = {};
  cfg.gridDim = dim3(128);
  cfg.blockDim = dim3(384);
  cfg.dynamicSmemBytes = SMEM_BYTES;
  cfg.stream = cudaStreamPerThread;
  cudaLaunchAttribute at[1];
  at[0].id = cudaLaunchAttributeClusterDimension;
  at[0].val.clusterDim.x = 2;
  at[0].val.clusterDim.y = 1;
  at[0].val.clusterDim.z = 1;
  cfg.attrs = at;
  cfg.numAttrs = 1;
  cudaLaunchKernelEx(&cfg, fused_kernel, m1, m3, m2, mh, mx, p, (__nv_bfloat16*)d_out);
}
```

```cpp
#include <cuda_runtime.h>
#include <cuda_bf16.h>
#include <cuda.h>
#include <stdint.h>

#define LAG1 4
#define LAG2 4
#define LAG3 3
#define HMC 0
#define GDELAY 1900
#define XDELAY 900
#define VARMODE 0
#define PACE 2048

namespace {

constexpr int L = 2048, D = 576, F = 4608, NMODE = 128;
constexpr int NS = 6;
constexpr uint32_t SLOT = 16384, BOX = 8192;
constexpr uint32_t OFF_STASH = NS * SLOT, STASH_STRIDE = 8 * BOX;
constexpr uint32_t OFF_BAR = NS * SLOT + 16 * BOX;
constexpr uint32_t B_G = OFF_BAR, B_PK = B_G + 8 * 2, B_XIN = B_PK + 8, B_LIN = B_XIN + 8 * 8, B_H = B_LIN + 8 * 4, B_UX = B_H + 8 * 10,
                   B_FULL = B_UX + 8, B_SE = B_FULL + 8 * NS, B_B8 = B_SE + 8 * 6, B_PRDY = B_B8 + 8,
                   B_DONE = B_PRDY + 8 * 2, B_SF = B_DONE + 8 * 2, B_EMPTY = B_SF + 8 * 10, B_CV = B_EMPTY + 8 * NS, B_END = B_CV + 8 * 2;
constexpr uint32_t OFF_MISC = OFF_BAR + 768;
constexpr uint32_t SMEM_BYTES = OFF_BAR + 1536;
constexpr uint32_t SPIN_LIMIT = 1u << 24;
static_assert(B_END <= OFF_BAR + 512, "barrier region");

constexpr uint32_t EARLY = 4;
constexpr uint32_t OFF_G = 0;
constexpr uint32_t OFF_WS = 2 * SLOT, WS_WARP = 7168, WS_KC = 4 * WS_WARP + 16, KC_PITCH = 1312, WS_BYTES = 32768;
constexpr uint32_t OFF_PART = EARLY * SLOT;
constexpr uint32_t OFF_U = OFF_WS + 3 * WS_BYTES, U_PAD = 384, U_PITCH = U_PAD + 4096;
constexpr uint32_t OFF_X = OFF_U + 5 * U_PITCH, X_PITCH = 4160;
constexpr uint32_t OFF_PK = OFF_X + 5 * X_PITCH, PK_PITCH = 8224;
constexpr uint32_t OFF_STG = OFF_PK + 5 * PK_PITCH, STG_PITCH = 2112;
static_assert(OFF_STG + 5 * STG_PITCH <= OFF_BAR, "front region");
static_assert(WS_KC + 2 * KC_PITCH <= WS_BYTES, "scratch");

struct Scratch {
  __nv_bfloat16 hT[D * L];
  uint4 part[16 * 8 * 3 * 2 * 512];
  uint4 part8[16 * 8 * 2 * 512];
  uint4 stats[3 * 256];
  unsigned flag[16 * 8 * 3 * 2];
  unsigned flag8[16 * 8];
  unsigned epoch[64];
};
__device__ __align__(1024) Scratch g_scratch;
#define STAMP(i)
#define STAMPC(c, i)

__device__ __forceinline__ int fresh_tid() {
  int t;
  asm volatile("mov.u32 %0, %tid.x;" : "=r"(t));
  return t;
}
__device__ __forceinline__ int warp_index() { return __shfl_sync(~0u, fresh_tid() >> 5, 0); }
__device__ __forceinline__ void mbar_init(uint32_t b, uint32_t c) {
  asm volatile("mbarrier.init.shared::cta.b64 [%0], %1;" ::"r"(b), "r"(c));
}
__device__ __forceinline__ void mbar_expect(uint32_t b, uint32_t n) {
  asm volatile("mbarrier.arrive.expect_tx.shared::cta.b64 _, [%0], %1;" ::"r"(b), "r"(n) : "memory");
}
__device__ __forceinline__ void mbar_arrive(uint32_t b) {
  asm volatile("mbarrier.arrive.shared::cta.b64 _, [%0];" ::"r"(b) : "memory");
}
__device__ __forceinline__ void mbar_arrive_cluster(uint32_t b) {
  asm volatile("mbarrier.arrive.shared::cluster.b64 _, [%0];" ::"r"(b) : "memory");
}
__device__ __forceinline__ void mbar_wait(uint32_t b, uint32_t parity) {
  asm volatile(
      "{\n.reg .pred p;\n.reg .u32 c;\nmov.u32 c, 0;\n"
      "WAIT:\nmbarrier.try_wait.parity.shared::cta.b64 p, [%0], %1;\n@p bra DONE;\n"
      "add.u32 c, c, 1;\nsetp.lt.u32 p, c, %2;\n@p bra WAIT;\ntrap;\nDONE:\n}\n" ::"r"(b), "r"(parity), "n"(SPIN_LIMIT) : "memory");
}
__device__ __forceinline__ bool elect_one() {
  uint32_t p;
  asm volatile("{\n.reg .pred p;\nelect.sync _|p, 0xffffffff;\nselp.u32 %0, 1, 0, p;\n}\n" : "=r"(p));
  return p != 0;
}
__device__ __forceinline__ void tma2d(uint32_t dst, const CUtensorMap* m, int c0, int c1, uint32_t bar) {
  asm volatile("cp.async.bulk.tensor.2d.shared::cluster.global.mbarrier::complete_tx::bytes [%0], [%1, {%3, %4}], [%2];"
               ::"r"(dst), "l"(m), "r"(bar), "r"(c0), "r"(c1) : "memory");
}
__device__ __forceinline__ void tma2d_mc(uint32_t dst, const CUtensorMap* m, int c0, int c1, uint32_t bar) {
  asm volatile(
      "cp.async.bulk.tensor.2d.shared::cluster.global.mbarrier::complete_tx::bytes.multicast::cluster [%0], [%1, {%3, %4}], [%2], %5;"
      ::"r"(dst), "l"(m), "r"(bar), "r"(c0), "r"(c1), "h"((uint16_t)3) : "memory");
}
__device__ __forceinline__ void bulk_load(uint32_t dst, const void* src, uint32_t bytes, uint32_t bar) {
  asm volatile("cp.async.bulk.shared::cluster.global.mbarrier::complete_tx::bytes [%0], [%1], %2, [%3];"
               ::"r"(dst), "l"(src), "r"(bytes), "r"(bar) : "memory");
}
__device__ __forceinline__ void bulk_store(void* dst, uint32_t src, uint32_t bytes) {
  asm volatile("cp.async.bulk.global.shared::cta.bulk_group [%0], [%1], %2;" ::"l"(dst), "r"(src), "r"(bytes) : "memory");
}
__device__ __forceinline__ void ldsm4t(uint32_t* r, uint32_t a) {
  asm volatile("ldmatrix.sync.aligned.m8n8.x4.trans.shared.b16 {%0,%1,%2,%3}, [%4];"
               : "=r"(r[0]), "=r"(r[1]), "=r"(r[2]), "=r"(r[3]) : "r"(a) : "memory");
}
__device__ __forceinline__ void ldsm4(uint32_t* r, uint32_t a) {
  asm volatile("ldmatrix.sync.aligned.m8n8.x4.shared.b16 {%0,%1,%2,%3}, [%4];"
               : "=r"(r[0]), "=r"(r[1]), "=r"(r[2]), "=r"(r[3]) : "r"(a) : "memory");
}
__device__ __forceinline__ void ldsm2t(uint32_t* r, uint32_t a) {
  asm volatile("ldmatrix.sync.aligned.m8n8.x2.trans.shared.b16 {%0,%1}, [%2];" : "=r"(r[0]), "=r"(r[1]) : "r"(a) : "memory");
}
__device__ __forceinline__ void st_async128(uint32_t a, const uint32_t* r, uint32_t bar) {
  asm volatile("st.async.weak.shared::cluster.mbarrier::complete_tx::bytes.v4.b32 [%0], {%1,%2,%3,%4}, [%5];"
               ::"r"(a), "r"(r[0]), "r"(r[1]), "r"(r[2]), "r"(r[3]), "r"(bar) : "memory");
}
__device__ __forceinline__ void ldsm2(uint32_t* r, uint32_t a) {
  asm volatile("ldmatrix.sync.aligned.m8n8.x2.shared.b16 {%0,%1}, [%2];" : "=r"(r[0]), "=r"(r[1]) : "r"(a) : "memory");
}
__device__ __forceinline__ void ldsm1(uint32_t* r, uint32_t a) {
  asm volatile("ldmatrix.sync.aligned.m8n8.x1.shared.b16 {%0}, [%1];" : "=r"(r[0]) : "r"(a) : "memory");
}
__device__ __forceinline__ void ldc128(uint32_t* r, uint32_t a) {
  asm volatile("ld.shared::cluster.v4.b32 {%0,%1,%2,%3}, [%4];" : "=r"(r[0]), "=r"(r[1]), "=r"(r[2]), "=r"(r[3]) : "r"(a) : "memory");
}
__device__ __forceinline__ void bulk_peer(uint32_t dst, uint32_t src, uint32_t bytes, uint32_t bar) {
  asm volatile("cp.async.bulk.shared::cluster.shared::cta.mbarrier::complete_tx::bytes [%0], [%1], %2, [%3];"
               ::"r"(dst), "r"(src), "r"(bytes), "r"(bar) : "memory");
}
__device__ __forceinline__ uint32_t mapa(uint32_t a, uint32_t rank) {
  uint32_t r;
  asm("mapa.shared::cluster.u32 %0, %1, %2;" : "=r"(r) : "r"(a), "r"(rank));
  return r;
}
__device__ __forceinline__ uint32_t lds32(uint32_t a) {
  uint32_t r;
  asm volatile("ld.shared.b32 %0, [%1];" : "=r"(r) : "r"(a) : "memory");
  return r;
}
__device__ __forceinline__ uint32_t lds16(uint32_t a) {
  uint32_t r;
  asm volatile("ld.shared.u16 %0, [%1];" : "=r"(r) : "r"(a) : "memory");
  return r;
}
__device__ __forceinline__ void lds64(uint32_t* r, uint32_t a) {
  asm volatile("ld.shared.v2.b32 {%0,%1}, [%2];" : "=r"(r[0]), "=r"(r[1]) : "r"(a) : "memory");
}
__device__ __forceinline__ void sts32(uint32_t a, uint32_t v) {
  asm volatile("st.shared.b32 [%0], %1;" ::"r"(a), "r"(v) : "memory");
}
__device__ __forceinline__ void sts16(uint32_t a, uint32_t v) {
  asm volatile("st.shared.u16 [%0], %1;" ::"r"(a), "r"(v) : "memory");
}
__device__ __forceinline__ void mma_bf16(float* c, uint32_t a0, uint32_t a1, uint32_t a2, uint32_t a3, const uint32_t* b) {
  asm volatile("mma.sync.aligned.m16n8k16.row.col.f32.bf16.bf16.f32 {%0,%1,%2,%3}, {%4,%5,%6,%7}, {%8,%9}, {%0,%1,%2,%3};"
               : "+f"(c[0]), "+f"(c[1]), "+f"(c[2]), "+f"(c[3])
               : "r"(a0), "r"(a1), "r"(a2), "r"(a3), "r"(b[0]), "r"(b[1]));
}
__device__ __forceinline__ void wg_bar(int wg) { asm volatile("bar.sync %0, 128;" ::"r"(wg + 1) : "memory"); }
__device__ __forceinline__ void stsm4(uint32_t a, const uint32_t* r) {
  asm volatile("stmatrix.sync.aligned.m8n8.x4.shared.b16 [%0], {%1,%2,%3,%4};"
               ::"r"(a), "r"(r[0]), "r"(r[1]), "r"(r[2]), "r"(r[3]) : "memory");
}
__device__ __forceinline__ void sts128(uint32_t a, const uint32_t* r) {
  asm volatile("st.shared.v4.b32 [%0], {%1,%2,%3,%4};" ::"r"(a), "r"(r[0]), "r"(r[1]), "r"(r[2]), "r"(r[3]) : "memory");
}
__device__ __forceinline__ void lds128(uint32_t* r, uint32_t a) {
  asm volatile("ld.shared.v4.b32 {%0,%1,%2,%3}, [%4];" : "=r"(r[0]), "=r"(r[1]), "=r"(r[2]), "=r"(r[3]) : "r"(a) : "memory");
}
__device__ __forceinline__ uint32_t pack_bf16(float lo, float hi) {
  uint32_t r;
  asm("cvt.rn.bf16x2.f32 %0, %1, %2;" : "=r"(r) : "f"(hi), "f"(lo));
  return r;
}
__device__ __forceinline__ float bf_lo(uint32_t v) { return __uint_as_float(v << 16); }
__device__ __forceinline__ float bf_hi(uint32_t v) { return __uint_as_float(v & 0xffff0000u); }
__device__ __forceinline__ float round_bf16(float v) { return __uint_as_float(pack_bf16(0.f, v)); }
__device__ __forceinline__ uint32_t sub_bf16x2(uint32_t a, uint32_t b) {
  uint32_t r;
  asm("sub.rn.bf16x2 %0, %1, %2;" : "=r"(r) : "r"(a), "r"(b));
  return r;
}
__device__ __forceinline__ uint32_t add_bf16x2(uint32_t a, uint32_t b) {
  uint32_t r;
  asm("add.rn.bf16x2 %0, %1, %2;" : "=r"(r) : "r"(a), "r"(b));
  return r;
}
__device__ __forceinline__ uint32_t mul_bf16x2(uint32_t a, uint32_t b) {
  uint32_t r;
  asm("mul.rn.bf16x2 %0, %1, %2;" : "=r"(r) : "r"(a), "r"(b));
  return r;
}
__device__ __forceinline__ uint32_t fma_bf16x2(uint32_t a, uint32_t b, uint32_t c) {
  uint32_t r;
  asm("fma.rn.bf16x2 %0, %1, %2, %3;" : "=r"(r) : "r"(a), "r"(b), "r"(c));
  return r;
}
__device__ __forceinline__ float ln_rstd(float var) {
  float sd, r;
  asm("sqrt.approx.ftz.f32 %0, %1;" : "=f"(sd) : "f"(round_bf16(round_bf16(var) + 1e-5f)));
  asm("rcp.approx.ftz.f32 %0, %1;" : "=f"(r) : "f"(round_bf16(sd)));
  return r;
}
__device__ __forceinline__ float tanh_hw(float x) {
  float r;
  asm("tanh.approx.f32 %0, %1;" : "=f"(r) : "f"(x));
  return r;
}
__device__ __forceinline__ unsigned ld_acquire(const unsigned* p) {
  unsigned v;
  asm volatile("ld.acquire.gpu.global.u32 %0, [%1];" : "=r"(v) : "l"(p) : "memory");
  return v;
}
__device__ __forceinline__ void wait_flag(const unsigned* p, unsigned target) {
  uint32_t c = 0;
  while ((int)(ld_acquire(p) - target) < 0) {
    if (++c > SPIN_LIMIT) __trap();
  }
}
__device__ __forceinline__ void red_add(unsigned* p, unsigned v) {
  asm volatile("red.relaxed.gpu.global.add.u32 [%0], %1;" ::"l"(p), "r"(v) : "memory");
}
#define WG_FENCE() asm volatile("wgmma.fence.sync.aligned;" ::: "memory")
#define WG_COMMIT() asm volatile("wgmma.commit_group.sync.aligned;" ::: "memory")
#define WG_WAIT(n) asm volatile("wgmma.wait_group.sync.aligned %0;" ::"n"(n) : "memory")

template <int TB>
__device__ __forceinline__ void wgmma_n16(float* d, const uint32_t* a, uint64_t db, int accum) {
  asm volatile(
      "{\n.reg .pred p;\nsetp.ne.b32 p, %13, 0;\n"
      "wgmma.mma_async.sync.aligned.m64n16k16.f32.bf16.bf16 "
      "{%0,%1,%2,%3,%4,%5,%6,%7}, "
      "{%8,%9,%10,%11}, %12, p, 1, 1, %14;\n}\n"
      : "+f"(d[0]), "+f"(d[1]), "+f"(d[2]), "+f"(d[3]), "+f"(d[4]), "+f"(d[5]), "+f"(d[6]), "+f"(d[7])
      : "r"(a[0]), "r"(a[1]), "r"(a[2]), "r"(a[3]), "l"(db), "r"(accum), "n"(TB));
}
template <int TB>
__device__ __forceinline__ void wgmma_n32(float* d, const uint32_t* a, uint64_t db, int accum) {
  asm volatile(
      "{\n.reg .pred p;\nsetp.ne.b32 p, %21, 0;\n"
      "wgmma.mma_async.sync.aligned.m64n32k16.f32.bf16.bf16 "
      "{%0,%1,%2,%3,%4,%5,%6,%7,%8,%9,%10,%11,%12,%13,%14,%15}, "
      "{%16,%17,%18,%19}, %20, p, 1, 1, %22;\n}\n"
      : "+f"(d[0]), "+f"(d[1]), "+f"(d[2]), "+f"(d[3]), "+f"(d[4]), "+f"(d[5]), "+f"(d[6]), "+f"(d[7]),
        "+f"(d[8]), "+f"(d[9]), "+f"(d[10]), "+f"(d[11]), "+f"(d[12]), "+f"(d[13]), "+f"(d[14]), "+f"(d[15])
      : "r"(a[0]), "r"(a[1]), "r"(a[2]), "r"(a[3]), "l"(db), "r"(accum), "n"(TB));
}
template <int TB>
__device__ __forceinline__ void wgmma_n48(float* d, const uint32_t* a, uint64_t db, int accum) {
  asm volatile(
      "{\n.reg .pred p;\nsetp.ne.b32 p, %29, 0;\n"
      "wgmma.mma_async.sync.aligned.m64n48k16.f32.bf16.bf16 "
      "{%0,%1,%2,%3,%4,%5,%6,%7,%8,%9,%10,%11,%12,%13,%14,%15,%16,%17,%18,%19,%20,%21,%22,%23}, "
      "{%24,%25,%26,%27}, %28, p, 1, 1, %30;\n}\n"
      : "+f"(d[0]), "+f"(d[1]), "+f"(d[2]), "+f"(d[3]), "+f"(d[4]), "+f"(d[5]), "+f"(d[6]), "+f"(d[7]),
        "+f"(d[8]), "+f"(d[9]), "+f"(d[10]), "+f"(d[11]), "+f"(d[12]), "+f"(d[13]), "+f"(d[14]), "+f"(d[15]),
        "+f"(d[16]), "+f"(d[17]), "+f"(d[18]), "+f"(d[19]), "+f"(d[20]), "+f"(d[21]), "+f"(d[22]), "+f"(d[23])
      : "r"(a[0]), "r"(a[1]), "r"(a[2]), "r"(a[3]), "l"(db), "r"(accum), "n"(TB));
}
template <int TB>
__device__ __forceinline__ void wgmma_n64(float* d, const uint32_t* a, uint64_t db, int accum) {
  asm volatile(
      "{\n.reg .pred p;\nsetp.ne.b32 p, %37, 0;\n"
      "wgmma.mma_async.sync.aligned.m64n64k16.f32.bf16.bf16 "
      "{%0,%1,%2,%3,%4,%5,%6,%7,%8,%9,%10,%11,%12,%13,%14,%15,%16,%17,%18,%19,%20,%21,%22,%23,%24,%25,%26,%27,%28,%29,%30,%31}, "
      "{%32,%33,%34,%35}, %36, p, 1, 1, %38;\n}\n"
      : "+f"(d[0]), "+f"(d[1]), "+f"(d[2]), "+f"(d[3]), "+f"(d[4]), "+f"(d[5]), "+f"(d[6]), "+f"(d[7]),
        "+f"(d[8]), "+f"(d[9]), "+f"(d[10]), "+f"(d[11]), "+f"(d[12]), "+f"(d[13]), "+f"(d[14]), "+f"(d[15]),
        "+f"(d[16]), "+f"(d[17]), "+f"(d[18]), "+f"(d[19]), "+f"(d[20]), "+f"(d[21]), "+f"(d[22]), "+f"(d[23]),
        "+f"(d[24]), "+f"(d[25]), "+f"(d[26]), "+f"(d[27]), "+f"(d[28]), "+f"(d[29]), "+f"(d[30]), "+f"(d[31])
      : "r"(a[0]), "r"(a[1]), "r"(a[2]), "r"(a[3]), "l"(db), "r"(accum), "n"(TB));
}
template <int TB>
__device__ __forceinline__ void wgmma_n80(float* d, const uint32_t* a, uint64_t db, int accum) {
  asm volatile(
      "{\n.reg .pred p;\nsetp.ne.b32 p, %45, 0;\n"
      "wgmma.mma_async.sync.aligned.m64n80k16.f32.bf16.bf16 "
      "{%0,%1,%2,%3,%4,%5,%6,%7,%8,%9,%10,%11,%12,%13,%14,%15,%16,%17,%18,%19,%20,%21,%22,%23,%24,%25,%26,%27,%28,%29,%30,%31,%32,%33,%34,%35,%36,%37,%38,%39}, "
      "{%40,%41,%42,%43}, %44, p, 1, 1, %46;\n}\n"
      : "+f"(d[0]), "+f"(d[1]), "+f"(d[2]), "+f"(d[3]), "+f"(d[4]), "+f"(d[5]), "+f"(d[6]), "+f"(d[7]),
        "+f"(d[8]), "+f"(d[9]), "+f"(d[10]), "+f"(d[11]), "+f"(d[12]), "+f"(d[13]), "+f"(d[14]), "+f"(d[15]),
        "+f"(d[16]), "+f"(d[17]), "+f"(d[18]), "+f"(d[19]), "+f"(d[20]), "+f"(d[21]), "+f"(d[22]), "+f"(d[23]),
        "+f"(d[24]), "+f"(d[25]), "+f"(d[26]), "+f"(d[27]), "+f"(d[28]), "+f"(d[29]), "+f"(d[30]), "+f"(d[31]),
        "+f"(d[32]), "+f"(d[33]), "+f"(d[34]), "+f"(d[35]), "+f"(d[36]), "+f"(d[37]), "+f"(d[38]), "+f"(d[39])
      : "r"(a[0]), "r"(a[1]), "r"(a[2]), "r"(a[3]), "l"(db), "r"(accum), "n"(TB));
}
template <int TB>
__device__ __forceinline__ void wgmma_n96(float* d, const uint32_t* a, uint64_t db, int accum) {
  asm volatile(
      "{\n.reg .pred p;\nsetp.ne.b32 p, %53, 0;\n"
      "wgmma.mma_async.sync.aligned.m64n96k16.f32.bf16.bf16 "
      "{%0,%1,%2,%3,%4,%5,%6,%7,%8,%9,%10,%11,%12,%13,%14,%15,%16,%17,%18,%19,%20,%21,%22,%23,%24,%25,%26,%27,%28,%29,%30,%31,%32,%33,%34,%35,%36,%37,%38,%39,%40,%41,%42,%43,%44,%45,%46,%47}, "
      "{%48,%49,%50,%51}, %52, p, 1, 1, %54;\n}\n"
      : "+f"(d[0]), "+f"(d[1]), "+f"(d[2]), "+f"(d[3]), "+f"(d[4]), "+f"(d[5]), "+f"(d[6]), "+f"(d[7]),
        "+f"(d[8]), "+f"(d[9]), "+f"(d[10]), "+f"(d[11]), "+f"(d[12]), "+f"(d[13]), "+f"(d[14]), "+f"(d[15]),
        "+f"(d[16]), "+f"(d[17]), "+f"(d[18]), "+f"(d[19]), "+f"(d[20]), "+f"(d[21]), "+f"(d[22]), "+f"(d[23]),
        "+f"(d[24]), "+f"(d[25]), "+f"(d[26]), "+f"(d[27]), "+f"(d[28]), "+f"(d[29]), "+f"(d[30]), "+f"(d[31]),
        "+f"(d[32]), "+f"(d[33]), "+f"(d[34]), "+f"(d[35]), "+f"(d[36]), "+f"(d[37]), "+f"(d[38]), "+f"(d[39]),
        "+f"(d[40]), "+f"(d[41]), "+f"(d[42]), "+f"(d[43]), "+f"(d[44]), "+f"(d[45]), "+f"(d[46]), "+f"(d[47])
      : "r"(a[0]), "r"(a[1]), "r"(a[2]), "r"(a[3]), "l"(db), "r"(accum), "n"(TB));
}
template <int TB>
__device__ __forceinline__ void wgmma_n112(float* d, const uint32_t* a, uint64_t db, int accum) {
  asm volatile(
      "{\n.reg .pred p;\nsetp.ne.b32 p, %61, 0;\n"
      "wgmma.mma_async.sync.aligned.m64n112k16.f32.bf16.bf16 "
      "{%0,%1,%2,%3,%4,%5,%6,%7,%8,%9,%10,%11,%12,%13,%14,%15,%16,%17,%18,%19,%20,%21,%22,%23,%24,%25,%26,%27,%28,%29,%30,%31,%32,%33,%34,%35,%36,%37,%38,%39,%40,%41,%42,%43,%44,%45,%46,%47,%48,%49,%50,%51,%52,%53,%54,%55}, "
      "{%56,%57,%58,%59}, %60, p, 1, 1, %62;\n}\n"
      : "+f"(d[0]), "+f"(d[1]), "+f"(d[2]), "+f"(d[3]), "+f"(d[4]), "+f"(d[5]), "+f"(d[6]), "+f"(d[7]),
        "+f"(d[8]), "+f"(d[9]), "+f"(d[10]), "+f"(d[11]), "+f"(d[12]), "+f"(d[13]), "+f"(d[14]), "+f"(d[15]),
        "+f"(d[16]), "+f"(d[17]), "+f"(d[18]), "+f"(d[19]), "+f"(d[20]), "+f"(d[21]), "+f"(d[22]), "+f"(d[23]),
        "+f"(d[24]), "+f"(d[25]), "+f"(d[26]), "+f"(d[27]), "+f"(d[28]), "+f"(d[29]), "+f"(d[30]), "+f"(d[31]),
        "+f"(d[32]), "+f"(d[33]), "+f"(d[34]), "+f"(d[35]), "+f"(d[36]), "+f"(d[37]), "+f"(d[38]), "+f"(d[39]),
        "+f"(d[40]), "+f"(d[41]), "+f"(d[42]), "+f"(d[43]), "+f"(d[44]), "+f"(d[45]), "+f"(d[46]), "+f"(d[47]),
        "+f"(d[48]), "+f"(d[49]), "+f"(d[50]), "+f"(d[51]), "+f"(d[52]), "+f"(d[53]), "+f"(d[54]), "+f"(d[55])
      : "r"(a[0]), "r"(a[1]), "r"(a[2]), "r"(a[3]), "l"(db), "r"(accum), "n"(TB));
}
template <int TB>
__device__ __forceinline__ void wgmma_n128(float* d, const uint32_t* a, uint64_t db, int accum) {
  asm volatile(
      "{\n.reg .pred p;\nsetp.ne.b32 p, %69, 0;\n"
      "wgmma.mma_async.sync.aligned.m64n128k16.f32.bf16.bf16 "
      "{%0,%1,%2,%3,%4,%5,%6,%7,%8,%9,%10,%11,%12,%13,%14,%15,%16,%17,%18,%19,%20,%21,%22,%23,%24,%25,%26,%27,%28,%29,%30,%31,%32,%33,%34,%35,%36,%37,%38,%39,%40,%41,%42,%43,%44,%45,%46,%47,%48,%49,%50,%51,%52,%53,%54,%55,%56,%57,%58,%59,%60,%61,%62,%63}, "
      "{%64,%65,%66,%67}, %68, p, 1, 1, %70;\n}\n"
      : "+f"(d[0]), "+f"(d[1]), "+f"(d[2]), "+f"(d[3]), "+f"(d[4]), "+f"(d[5]), "+f"(d[6]), "+f"(d[7]),
        "+f"(d[8]), "+f"(d[9]), "+f"(d[10]), "+f"(d[11]), "+f"(d[12]), "+f"(d[13]), "+f"(d[14]), "+f"(d[15]),
        "+f"(d[16]), "+f"(d[17]), "+f"(d[18]), "+f"(d[19]), "+f"(d[20]), "+f"(d[21]), "+f"(d[22]), "+f"(d[23]),
        "+f"(d[24]), "+f"(d[25]), "+f"(d[26]), "+f"(d[27]), "+f"(d[28]), "+f"(d[29]), "+f"(d[30]), "+f"(d[31]),
        "+f"(d[32]), "+f"(d[33]), "+f"(d[34]), "+f"(d[35]), "+f"(d[36]), "+f"(d[37]), "+f"(d[38]), "+f"(d[39]),
        "+f"(d[40]), "+f"(d[41]), "+f"(d[42]), "+f"(d[43]), "+f"(d[44]), "+f"(d[45]), "+f"(d[46]), "+f"(d[47]),
        "+f"(d[48]), "+f"(d[49]), "+f"(d[50]), "+f"(d[51]), "+f"(d[52]), "+f"(d[53]), "+f"(d[54]), "+f"(d[55]),
        "+f"(d[56]), "+f"(d[57]), "+f"(d[58]), "+f"(d[59]), "+f"(d[60]), "+f"(d[61]), "+f"(d[62]), "+f"(d[63])
      : "r"(a[0]), "r"(a[1]), "r"(a[2]), "r"(a[3]), "l"(db), "r"(accum), "n"(TB));
}
template <int N, int TB>
__device__ __forceinline__ void wgmma_rs(float* d, const uint32_t* a, uint64_t db, int accum) {
  if constexpr (N == 16) wgmma_n16<TB>(d, a, db, accum);
  if constexpr (N == 32) wgmma_n32<TB>(d, a, db, accum);
  if constexpr (N == 48) wgmma_n48<TB>(d, a, db, accum);
  if constexpr (N == 64) wgmma_n64<TB>(d, a, db, accum);
  if constexpr (N == 80) wgmma_n80<TB>(d, a, db, accum);
  if constexpr (N == 96) wgmma_n96<TB>(d, a, db, accum);
  if constexpr (N == 112) wgmma_n112<TB>(d, a, db, accum);
  if constexpr (N == 128) wgmma_n128<TB>(d, a, db, accum);
}

struct SsmParams {
  const __nv_bfloat16 *x, *a_re, *a_im, *b_re, *b_im, *c_re, *c_im, *log_dt, *dskip, *w1, *w3, *w2;
  Scratch* g;
};
struct C2 {
  float r, i;
};
__device__ __forceinline__ C2 cmul(C2 a, C2 b) { return {fmaf(a.r, b.r, -a.i * b.i), fmaf(a.r, b.i, a.i * b.r)}; }
__device__ __forceinline__ C2 cmulc(C2 a, C2 b) { return {fmaf(a.r, b.r, a.i * b.i), fmaf(a.i, b.r, -a.r * b.i)}; }
__device__ __forceinline__ C2 cexp_pow(float a2, float rev, float l) {
  float m, t = rev * l, sn, cs;
  asm("ex2.approx.ftz.f32 %0, %1;" : "=f"(m) : "f"(a2 * l));
  t = (t - rintf(t)) * 6.283185307179586f;
  asm("sin.approx.ftz.f32 %0, %1;" : "=f"(sn) : "f"(t));
  asm("cos.approx.ftz.f32 %0, %1;" : "=f"(cs) : "f"(t));
  return {m * cs, m * sn};
}
__device__ __forceinline__ void store8(uint32_t addr, const C2* v) {
  uint32_t re[4], im[4];
#pragma unroll
  for (int i = 0; i < 4; i++) {
    re[i] = pack_bf16(v[2 * i].r, v[2 * i + 1].r);
    im[i] = pack_bf16(v[2 * i].i, v[2 * i + 1].i);
  }
  sts128(addr, re);
  sts128(addr + WS_WARP / 2, im);
}
struct ModeIn {
  uint32_t ar, ai, br, bi, cr, ci, ldt;
};
__device__ __forceinline__ uint32_t ldg16(const __nv_bfloat16* p) {
  uint32_t r;
  asm volatile("ld.global.nc.u16 %0, [%1];" : "=r"(r) : "l"(p));
  return r;
}
__device__ __forceinline__ uint32_t ldg32(const __nv_bfloat16* p) {
  uint32_t r;
  asm volatile("ld.global.nc.u32 %0, [%1];" : "=r"(r) : "l"(p));
  return r;
}
__device__ __forceinline__ ModeIn load_modes(const SsmParams& p, uint32_t d, uint32_t pair) {
  const uint32_t i = d * NMODE + 2 * pair;
  return {ldg32(p.a_re + i), ldg32(p.a_im + i), ldg32(p.b_re + i), ldg32(p.b_im + i),
          ldg32(p.c_re + i), ldg32(p.c_im + i), ldg16(p.log_dt + d)};
}

__device__ __forceinline__ void kgen_modes(uint32_t my, const ModeIn in, uint32_t sel, float (&acc)[6][4]) {
  const int lane = fresh_tid() & 31;
  const uint32_t row = my + lane * 112;
  auto pick = [&](uint32_t v) { return __uint_as_float(__byte_perm(v, 0, sel)); };
  const float dt = round_bf16(__expf(bf_lo(in.ldt)));
  const float a2 = dt * pick(in.ar) * 1.4426950408889634f, rev = dt * pick(in.ai) * 0.15915494309189535f;
  const C2 e1 = cexp_pow(a2, rev, 1.f), e8 = cexp_pow(a2, rev, 8.f), e256 = cexp_pow(a2, rev, 256.f);
  {
    C2 y[8];
    y[0] = {1.f, 0.f};
    y[1] = e8;
    y[2] = cmul(e8, e8);
    y[3] = cmul(y[2], e8);
    y[4] = cmul(y[2], y[2]);
    y[5] = cmul(y[4], y[1]);
    y[6] = cmul(y[4], y[2]);
    y[7] = cmul(y[4], y[3]);
    const C2 e64 = cmul(y[4], y[4]);
    store8(row, y);
#pragma unroll
    for (int c = 1; c < 4; c++) {
#pragma unroll
      for (int i = 0; i < 8; i++) y[i] = (c == 1 && i == 0) ? e64 : cmul(y[i], e64);
      store8(row + 16 * c, y);
    }
  }
  {
    C2 x[8], z[8];
    x[0] = cmulc({pick(in.cr), -pick(in.ci)}, {dt * pick(in.br), dt * pick(in.bi)});
    x[1] = cmulc(x[0], e1);
    const C2 e2 = cmul(e1, e1);
#pragma unroll
    for (int i = 2; i < 8; i++) x[i] = cmulc(x[i - 2], e2);
    store8(row + 64, x);
#pragma unroll
    for (int i = 0; i < 4; i++) z[i] = cmulc(x[2 * i], e256);
    z[4] = cmulc(z[0], e256);
    z[5] = cmulc(z[2], e256);
    z[6] = cmulc(z[4], e256);
    z[7] = cmulc(z[5], e256);
    store8(row + 80, z);
    const C2 e512 = cmul(e256, e256);
    x[0] = cmulc(z[4], e512);
    x[1] = cmulc(z[6], e512);
    x[2] = cmulc(x[0], e512);
    x[3] = cmulc(x[1], e512);
    x[4] = cmulc(x[2], e512);
    x[5] = x[6] = x[7] = {0.f, 0.f};
    store8(row + 96, x);
  }
  __syncwarp();
  const uint32_t aa = my + (lane >> 4) * (WS_WARP / 2) + (lane & 7) * 112 + ((lane >> 3) & 1) * 16;
  const uint32_t ba = my + ((lane >> 3) & 1) * (WS_WARP / 2) + (lane & 7) * 112 + (lane >> 4) * 16 + 64;
#pragma unroll
  for (int ks = 0; ks < 4; ks++) {
    uint32_t a[2][4], b[6];
    ldsm4t(a[0], aa + ks * 896);
    ldsm4t(a[1], aa + ks * 896 + 32);
    ldsm4t(b, ba + ks * 896);
    ldsm2t(b + 4, ba + ks * 896 + 32);
#pragma unroll
    for (int nt = 0; nt < 3; nt++)
#pragma unroll
      for (int mt = 0; mt < 2; mt++) mma_bf16(acc[nt * 2 + mt], a[mt][0], a[mt][1], a[mt][2], a[mt][3], &b[2 * nt]);
  }
  __syncwarp();
}

__device__ __forceinline__ void stats_load(Scratch* g, uint32_t (&st)[12]) {
  const uint4* sp = &g->stats[fresh_tid()];
#pragma unroll
  for (int e = 0; e < 3; e++) {
    uint32_t* v = &st[4 * e];
    asm volatile("ld.relaxed.gpu.global.v4.b32 {%0,%1,%2,%3}, [%4];"
                 : "=r"(v[0]), "=r"(v[1]), "=r"(v[2]), "=r"(v[3]) : "l"(sp + 256 * e) : "memory");
  }
}
__device__ __forceinline__ void kgen_finish(uint32_t sb, Scratch* g, int wg, const float (&acc)[6][4], uint32_t (&st)[12]) {
  const int t = fresh_tid() & 127;
  const uint32_t ws = sb + OFF_WS + wg * WS_BYTES;
#pragma unroll
  for (int i = 0; i < 6; i++)
    sts128(ws + (t >> 5) * WS_WARP + i * 512 + (t & 31) * 16, reinterpret_cast<const uint32_t*>(acc[i]));
  if (t < 2) sts32(ws + WS_KC - 4 + t * KC_PITCH, 0);
  STAMPC(threadIdx.x == 0, 15);
  wg_bar(wg);
  STAMPC(threadIdx.x == 0, 16);
  {
    uint32_t v[3][4][2], pk[3][2];
#pragma unroll
    for (int k = 0; k < 3; k++)
#pragma unroll
      for (int src = 0; src < 4; src++) lds64(v[k][src], ws + src * WS_WARP + k * 1024 + t * 8);
    const float f = wg == 2 ? 1.f : 0.f;
#pragma unroll
    for (int k = 0; k < 3; k++) {
      const float b0 = __uint_as_float(v[k][2][0]) + __uint_as_float(v[k][3][0]);
      const float b1 = __uint_as_float(v[k][2][1]) + __uint_as_float(v[k][3][1]);
      const float a0 = __uint_as_float(v[k][0][0]) + __uint_as_float(v[k][1][0]);
      const float a1 = __uint_as_float(v[k][0][1]) + __uint_as_float(v[k][1][1]);
      pk[k][0] = f != 0.f ? pack_bf16(a0 + b0, a1 + b1) : pack_bf16(a0, a1);
      pk[k][1] = pack_bf16(b0, b1);
    }
    const int q = (t >> 1) & 3, j = (t >> 6) * 16 + ((t >> 3) & 7) + (t & 1) * 8;
#pragma unroll
    for (int ch = 0; ch < 2; ch++) {
      const uint32_t kc = ws + WS_KC + ch * KC_PITCH;
      sts32(kc + 2 * (8 * j + 2 * q), pk[0][ch]);
      sts32(kc + 2 * (q < 2 ? 256 + 4 * j + 2 * q : 256 + 64 * q + 2 * j), pk[1][ch]);
      if (q < 2 || (q == 2 && j == 0)) sts16(kc + 2 * (512 + 64 * q + j), pk[2][ch]);
      if (q < 2) sts16(kc + 2 * (544 + 64 * q + j), pk[2][ch] >> 16);
    }
  }
  wg_bar(wg);
  STAMPC(threadIdx.x == 0, 17);
  if (wg < 2) stats_load(g, st);
  uint32_t v[2][9];
  const bool dense = t < 64;
#pragma unroll
  for (int ch = 0; ch < 2; ch++) {
    const uint32_t kc = ws + WS_KC + ch * KC_PITCH, k0 = kc + (dense ? 8 * t : 256 + 4 * t);
    v[ch][0] = lds32(k0);
    v[ch][1] = lds32(k0 + 4);
    v[ch][2] = lds16(k0 - (t <= 64 ? 2 : 0));
    v[ch][3] = lds16(kc + 2 * (384 + t));
    v[ch][4] = lds16(kc + 2 * (385 + t));
#pragma unroll
    for (int k = 0; k < 2; k++) {
      v[ch][5 + 2 * k] = lds16(kc + 2 * (512 + 64 * k + (t >> 1)));
      v[ch][6 + 2 * k] = lds16(kc + 2 * (512 + 64 * k + ((t + 1) >> 1)));
    }
  }
  const uint32_t s1 = dense ? 0x1032 : 0x1010, s2 = dense ? 0x7610 : 0x5476, s3 = dense ? 0x1032 : 0x7610;
#pragma unroll
  for (int ch = 0; ch < 2; ch++) {
    if (ch == 1 && wg == 2) break;
    const uint32_t pkb = sb + OFF_PK + (2 * wg + ch) * PK_PITCH + 32 + t * 16;
    uint32_t o[4];
    o[0] = __byte_perm(v[ch][0], v[ch][2], 0x5410);
    o[1] = __byte_perm(v[ch][0], 0, s1);
    o[2] = __byte_perm(v[ch][1], v[ch][0], s2);
    o[3] = __byte_perm(v[ch][1], v[ch][0], s3);
    sts128(pkb, o);
    uint32_t vm = (t & 1) ? v[ch][4] : v[ch][3];
    o[0] = o[1] = __byte_perm(v[ch][3], 0, 0x1010);
    o[2] = __byte_perm(vm, v[ch][3], 0x5410);
    o[3] = __byte_perm(v[ch][4], vm, 0x5410);
    sts128(pkb + 2048, o);
#pragma unroll
    for (int k = 0; k < 2; k++) {
      const uint32_t v0 = v[ch][5 + 2 * k], v1 = v[ch][6 + 2 * k];
      vm = (t & 2) ? v1 : v0;
      o[0] = __byte_perm(vm, v0, 0x5410);
      o[1] = __byte_perm(v1, vm, 0x5410);
      o[2] = o[3] = __byte_perm(v1, 0, 0x1010);
      sts128(pkb + 4096 + 2048 * k, o);
    }
  }
}

__device__ __forceinline__ uint32_t copy_reg(uint32_t v) {
  uint32_t r;
  asm volatile("mov.b32 %0, %1;" : "=r"(r) : "r"(v));
  return r;
}
struct ConvCtx {
  uint32_t pa, pw, pr, ub, xb, dsk;
  uint64_t db;
  uint4* hrow;
  int wg, t;
  uint32_t sig;
};
__device__ __forceinline__ void conv_emit(const ConvCtx& c, int k) {
  uint32_t v[6][4], h[4];
  wg_bar(c.wg);
#pragma unroll
  for (int src = 0; src < 4; src++) lds128(v[src], k == 0 && c.t < src ? c.ub - 64 : c.pr + src * 4080 + 2048 * k);
  lds128(v[4], c.ub + 2048 * k);
  lds128(v[5], c.xb + 2048 * k);
#pragma unroll
  for (int e = 0; e < 4; e++) {
    const uint32_t y = add_bf16x2(add_bf16x2(v[0][e], v[1][e]), add_bf16x2(v[2][e], v[3][e]));
    h[e] = add_bf16x2(v[5][e], add_bf16x2(y, mul_bf16x2(v[4][e], c.dsk)));
  }
  c.hrow[128 * k] = make_uint4(h[0], h[1], h[2], h[3]);
}
__device__ __forceinline__ void conv_spill(const ConvCtx& c, const float* acc, int b) {
  uint32_t p[4];
#pragma unroll
  for (int e = 0; e < 4; e++) p[e] = pack_bf16(acc[2 * e], acc[2 * e + 1]);
  asm volatile("stmatrix.sync.aligned.m8n8.x4.trans.shared.b16 [%0], {%1,%2,%3,%4};"
               ::"r"(c.pw + b * 512), "r"(p[0]), "r"(p[1]), "r"(p[2]), "r"(p[3]) : "memory");
}
template <int B>
__device__ __forceinline__ void conv_batches(const ConvCtx& c, float (&acc)[64], uint32_t (&a)[2][4][4]) {
  constexpr int N = (B + 1) & 1;
  WG_FENCE();
#pragma unroll
  for (int k = 0; k < 4; k++) wgmma_rs<128 - 16 * B, 0>(acc + 8 * B, a[B & 1][k], c.db - 16 * (k >> 1) - 4 * (k & 1), B + k);
  WG_COMMIT();
  if constexpr (B < 7) {
#pragma unroll
    for (int k = 0; k < 4; k++) {
      const uint32_t o = c.pa + 1024 * (B + 1) + 512 * (k >> 1) + 128 * (k & 1);
      a[N][k][0] = lds32(o);
      a[N][k][1] = lds32(o + 256);
    }
  }
  if constexpr (B == 0) wg_bar(c.wg);
  if constexpr (B > 0) conv_spill(c, acc + 8 * (B - 1), B - 1);
  if constexpr (B == 4) {
    conv_emit(c, 0);
    __syncwarp();
    if (c.sig) mbar_arrive(c.sig);
  }
  WG_WAIT(0);
#pragma unroll
  for (int i = 8 * B; i < 64; i++) asm volatile("mov.b32 %0, %1;" : "=f"(acc[i]) : "f"(acc[i]));
  if constexpr (B < 7) {
#pragma unroll
    for (int k = 0; k < 4; k++) {
      a[N][k][2] = copy_reg(k < 2 ? a[B & 1][k + 2][1] : a[N][k - 2][1]);
      a[N][k][3] = copy_reg(a[N][k][0]);
    }
    conv_batches<B + 1>(c, acc, a);
  }
}

__device__ __forceinline__ void conv_task(uint32_t sb, Scratch* g, int wg, int w, int local, int d) {
  const int t = fresh_tid() & 127, lane = t & 31;
  const uint32_t ub = sb + OFF_U + local * U_PITCH + U_PAD, part = sb + OFF_PART + wg * SLOT;
  ConvCtx c;
  c.pa = sb + OFF_PK + local * PK_PITCH + 32 + 4 * (8 * w + (lane >> 2) - 2 * (lane & 3));
  c.pw = part + w * 4096 + lane * 16;
  c.pr = part + 16 * t;
  c.ub = ub + 16 * t;
  c.xb = sb + OFF_X + local * X_PITCH + 16 * t;
  c.dsk = lds32(sb + OFF_MISC + 128 + 4 * local);
  c.db = (uint64_t)((ub & 0x3FFFF) >> 4) | ((uint64_t)(128 >> 4) << 16) | ((uint64_t)(256 >> 4) << 32);
  c.hrow = reinterpret_cast<uint4*>(g->hT + d * L) + t;
  c.wg = wg;
  c.t = t;
  c.sig = (local & 1) && lane == 0 ? sb + B_CV : 0;
  float acc[64];
  uint32_t a[2][4][4];
#pragma unroll
  for (int k = 0; k < 4; k++) {
    const uint32_t o = c.pa + 512 * (k >> 1) + 128 * (k & 1);
    a[0][k][0] = lds32(o);
    a[0][k][1] = lds32(o + 256);
    a[0][k][2] = copy_reg(k < 2 ? 0 : a[0][k & 1][1]);
    a[0][k][3] = copy_reg(a[0][k][0]);
  }
  conv_batches<0>(c, acc, a);
  STAMP(32 + wg + 3 * (local & 1));
  conv_spill(c, acc + 56, 7);
  conv_emit(c, 1);
}

__device__ __forceinline__ void mma_k8(float* c, uint32_t a0, uint32_t a1, uint32_t b) {
  asm volatile("mma.sync.aligned.m16n8k8.row.col.f32.bf16.bf16.f32 {%0,%1,%2,%3}, {%4,%5}, {%6}, {%0,%1,%2,%3};"
               : "+f"(c[0]), "+f"(c[1]), "+f"(c[2]), "+f"(c[3]) : "r"(a0), "r"(a1), "r"(b));
}

__device__ __forceinline__ void ln1_stats(uint32_t sb, Scratch* g, int c, const uint4 (&xv)[9]) {
  const int t = fresh_tid() & 127, lane = t & 31;
  float st[5][4];
#pragma unroll
  for (int i = 0; i < 5; i++) st[i][0] = st[i][1] = st[i][2] = st[i][3] = 0.f;
  const uint32_t ones[2] = {0x3f803f80u, 0x3f803f80u};
  STAMPC(t == 0 && xv[0].x != 0x12345, 44);
#pragma unroll
  for (int i = 0; i < 9; i++) {
    mma_bf16(st[0], xv[i].x, xv[i].y, xv[i].z, xv[i].w, ones);
    mma_k8(st[1], xv[i].x, xv[i].y, xv[i].x);
    mma_k8(st[2], xv[i].x, xv[i].y, xv[i].y);
    mma_k8(st[3], xv[i].z, xv[i].w, xv[i].z);
    mma_k8(st[4], xv[i].z, xv[i].w, xv[i].w);
  }
  float s = st[0][0] + st[0][2];
  float q = (lane & 4) ? (st[1][1] + st[3][1]) + (st[2][3] + st[4][3]) : (st[1][0] + st[3][0]) + (st[2][2] + st[4][2]);
  STAMPC(t == 0 && q != 1234.f, 45);
  s += __shfl_xor_sync(~0u, s, 4);
  q += __shfl_xor_sync(~0u, q, 4);
  q = __shfl_sync(~0u, q, (lane & 24) + (lane >> 3));
  const float m = s * (1.f / D), r = ln_rstd(fmaxf(q * (1.f / D) - m * m, 0.f));
  const int sub = t & 7;
  const uint32_t b = pack_bf16(sub == 0 ? m : sub == 1 ? r : r - round_bf16(r), 0.f);
  if (sub < 3) sts16(sb + OFF_MISC + sub * 32 + (t >> 3) * 2, b ? b : 0x8000u);
  wg_bar(2);
  if (t < 6) {
    uint32_t v[4];
    lds128(v, sb + OFF_MISC + t * 16);
    asm volatile("st.relaxed.gpu.global.v4.b32 [%0], {%1,%2,%3,%4};" ::"l"(&g->stats[(t >> 1) * 256 + 2 * c + (t & 1)]),
                 "r"(v[0]), "r"(v[1]), "r"(v[2]), "r"(v[3]) : "memory");
  }
}

__device__ __forceinline__ void x_transpose(uint32_t sb, int c, int w) {
  const int lane = fresh_tid() & 31, rank = c & 1;
  uint32_t dx[2];
#pragma unroll
  for (int hf = 0; hf < 2; hf++) {
    const int rel = 8 * hf + (lane >> 2) - ((c >> 1) & 7), loc = rel > 4 ? rel - 5 : rel;
    dx[hf] = (rel > 4) == rank ? OFF_X + loc * X_PITCH + 2048 * rank : OFF_STG + loc * STG_PITCH;
    dx[hf] = rel >= 0 && rel < 9 ? sb + dx[hf] + 16 * (lane & 3) + 64 * w : 0;
  }
#pragma unroll 1
  for (int half = 0; half < 2; half++) {
    mbar_wait(sb + B_G + 8 * half, 0);
    STAMPC(w == 0 && lane == 0, 56 + half);
    uint32_t x[8][4];
#pragma unroll
    for (int i = 0; i < 8; i++)
      ldsm4t(x[i], sb + OFF_G + (16 * half + 4 * (i >> 1) + w) * 1024 + lane * 32 + (((i ^ (lane >> 2)) & 1) << 4));
#pragma unroll
    for (int i = 0; i < 8; i++)
      if (dx[i & 1]) sts128(dx[i & 1] + 1024 * half + 256 * (i >> 1), x[i]);
  }
  asm volatile("fence.proxy.async.shared::cta;" ::: "memory");
  wg_bar(2);
  if (elect_one()) {
    const uint32_t pb = mapa(sb, rank ^ 1), dst = pb + OFF_X + 2048 * rank;
    bulk_peer(dst + w * X_PITCH, sb + OFF_STG + w * STG_PITCH, 2048, pb + B_UX);
    if (w == 0) bulk_peer(dst + 4 * X_PITCH, sb + OFF_STG + 4 * STG_PITCH, 2048, pb + B_UX);
    if (w == 1) mbar_arrive(sb + B_UX);
  }
  __syncwarp();
}

__device__ __forceinline__ void ln1_apply(uint32_t sb, Scratch* g, uint32_t (&st)[12]) {
  const int t = fresh_tid();
  for (uint32_t spins = 0;; spins++) {
    uint32_t mn = ~0u;
#pragma unroll
    for (int e = 0; e < 12; e++) mn = min(mn, st[e]);
    if (__all_sync(~0u, mn != 0)) break;
    if (spins > SPIN_LIMIT) __trap();
    stats_load(g, st);
  }
  STAMPC(t == 0, 60);
  mbar_wait(sb + B_UX, 0);
  STAMPC(t == 0, 61);
  uint32_t x[5][4];
#pragma unroll
  for (int ch = 0; ch < 5; ch++) lds128(x[ch], sb + OFF_X + ch * X_PITCH + 16 * t);
#pragma unroll
  for (int ch = 0; ch < 5; ch++) {
#pragma unroll
    for (int e = 0; e < 4; e++) {
      const uint32_t dv = sub_bf16x2(x[ch][e], st[e]);
      x[ch][e] = fma_bf16x2(dv, st[4 + e], mul_bf16x2(dv, st[8 + e]));
    }
    sts128(sb + OFF_U + ch * U_PITCH + U_PAD + 16 * t, x[ch]);
  }
}

struct Ring {
  uint32_t slot, phase;
  __device__ __forceinline__ uint32_t off() const { return slot * SLOT; }
  __device__ __forceinline__ void next() {
    if (++slot == NS) { slot = 0; phase ^= 1; }
  }
};

__device__ __forceinline__ uint64_t bdesc(uint32_t addr) {
  return (uint64_t)((addr & 0x3FFFF) >> 4) | ((uint64_t)(BOX >> 4) << 16) | ((uint64_t)(1024 >> 4) << 32) | (1ull << 62);
}
__device__ __forceinline__ void release_slot(uint32_t sb, uint32_t slot, int lane) {
  if (lane == 0) mbar_arrive(sb + B_EMPTY + 8 * slot);
}
__device__ __forceinline__ void add_partial(float* sum, uint32_t addr) {
#pragma unroll
  for (int j = 0; j < 4; j++) {
    uint32_t v[4];
    lds128(v, addr + j * 512);
#pragma unroll
    for (int i = 0; i < 4; i++) {
      sum[8 * j + 2 * i] += bf_lo(v[i]);
      sum[8 * j + 2 * i + 1] += bf_hi(v[i]);
      asm volatile("" : "+f"(sum[8 * j + 2 * i]), "+f"(sum[8 * j + 2 * i + 1]));
    }
  }
}
__device__ __forceinline__ void stage_partial(const float* acc, uint32_t addr) {
#pragma unroll
  for (int j = 0; j < 4; j++) {
    uint32_t p[4];
#pragma unroll
    for (int i = 0; i < 4; i++) p[i] = pack_bf16(acc[8 * j + 2 * i], acc[8 * j + 2 * i + 1]);
    sts128(addr + j * 512, p);
  }
}
__device__ __forceinline__ void stage_done(uint32_t bar, int lane) {
  asm volatile("fence.proxy.async.shared::cta;" ::: "memory");
  __syncwarp();
  if (lane == 0) mbar_arrive(bar);
}
__device__ __forceinline__ void lag_sync(int wg) {
  if (wg == 1) asm volatile("bar.sync 4, 256;" ::: "memory");
}
__device__ __forceinline__ void lag_arrive(int wg) {
  if (wg == 0) asm volatile("bar.arrive 4, 256;" ::: "memory");
}

__device__ __forceinline__ void load_partial(float* sum, uint32_t addr) {
#pragma unroll
  for (int j = 0; j < 4; j++) {
    uint32_t v[4];
    lds128(v, addr + j * 512);
#pragma unroll
    for (int i = 0; i < 4; i++) {
      sum[8 * j + 2 * i] = bf_lo(v[i]);
      sum[8 * j + 2 * i + 1] = bf_hi(v[i]);
    }
  }
}

template <int T, typename Fn>
__device__ __forceinline__ void step64(float (&acc)[32], const uint32_t (&A)[144], uint32_t sb, uint64_t desc0, Ring& ring,
                                       int wg, int lane, Fn&& side) {
  uint32_t prev = 0;
#pragma unroll
  for (int st = 0; st < 5; st++) {
    mbar_wait(sb + B_FULL + 8 * ring.slot, ring.phase);
    const uint64_t db = desc0 + (ring.off() >> 4);
    if (st == 5 - LAG3) lag_sync(wg);
    WG_FENCE();
#pragma unroll
    for (int k = 0; k < (st < 4 ? 8 : 4); k++) wgmma_rs<64, 1>(acc, &A[(st * 8 + k) * 4], db + k * 128, st + k);
    WG_COMMIT();
    if (st == 4) lag_arrive(wg);
    if (st > 0 && T * 5 + st - 1 < 15 - NS) {
      WG_WAIT(1);
      release_slot(sb, prev, lane);
    }
    prev = ring.slot;
    ring.next();
    side(st);
  }
  WG_WAIT(0);
  if (T * 5 + 4 < 15 - NS) release_slot(sb, prev, lane);
}

__device__ __forceinline__ void ffn_consumer(uint32_t sb, Scratch* g, int warp, int r, int s, __nv_bfloat16* __restrict__ out) {
  const int tid = fresh_tid(), wg = warp >> 2, w = warp & 3, lane = tid & 31;
  const uint32_t stash = OFF_STASH + wg * STASH_STRIDE;
  const uint32_t priv = sb + stash + w * 2048 + lane * 16;
  uint32_t A[144];
  float rs0, rs1;
  const uint32_t tr_off = ((lane >> 4) * 8 + (lane & 7)) * 128 + (((2 * w + ((lane >> 3) & 1)) ^ (lane & 7)) << 4);
  {
    float st[6][4];
#pragma unroll
    for (int i = 0; i < 6; i++) st[i][0] = st[i][1] = st[i][2] = st[i][3] = 0.f;
    const uint32_t ones[2] = {0x3f803f80u, 0x3f803f80u};
#pragma unroll
    for (int kb = 0; kb < 9; kb++) {
      if (kb == 0 || (kb & 1)) mbar_wait(sb + B_H + 8 * (wg * 5 + (kb + 1) / 2), 0);
      const uint32_t box = sb + (kb ? stash + (kb - 1) * BOX : (NS - 1) * SLOT + wg * BOX) + tr_off;
#pragma unroll
      for (int k = 0; k < 4; k++) {
        uint32_t* a = &A[(kb * 4 + k) * 4];
        ldsm4t(a, box + k * 2048);
        const uint32_t bt[4] = {a[0], a[2], a[1], a[3]};
        mma_bf16(st[3 * (k & 1)], a[0], a[1], a[2], a[3], ones);
        mma_bf16(st[3 * (k & 1) + 1], a[0], a[1], a[2], a[3], bt);
        mma_bf16(st[3 * (k & 1) + 2], a[0], a[1], a[2], a[3], bt + 2);
      }
      if (kb == 2) release_slot(sb, NS - 1, lane);
      if (kb == 0) STAMP(24 + wg);
      if (kb == 8) STAMP(26 + wg);
    }
    const bool odd = (lane >> 2) & 1;
    const int dsrc = (lane & 28) + (lane >> 3);
    const float q0 = __shfl_sync(~0u, odd ? st[1][1] + st[4][1] : st[1][0] + st[4][0], dsrc);
    const float q1 = __shfl_sync(~0u, odd ? st[2][3] + st[5][3] : st[2][2] + st[5][2], dsrc);
    const float m0 = (st[0][0] + st[3][0]) * (1.f / D), m1 = (st[0][2] + st[3][2]) * (1.f / D);
    if (wg == 1) asm volatile("bar.arrive 6, 256;" ::: "memory");
    rs0 = ln_rstd(fmaxf(q0 * (1.f / D) - m0 * m0, 0.f));
    rs1 = ln_rstd(fmaxf(q1 * (1.f / D) - m1 * m1, 0.f));
    const uint32_t mm0 = pack_bf16(m0, m0), mm1 = pack_bf16(m1, m1);
#pragma unroll
    for (int i = 0; i < 144; i++) {
      A[i] = sub_bf16x2(A[i], (i & 1) ? mm1 : mm0);
    }
    if (warp == s && (lane & 3) == 0) {
      sts32(sb + OFF_MISC + 160 + lane, __float_as_uint(rs0));
      sts32(sb + OFF_MISC + 192 + lane, __float_as_uint(rs1));
    }
  }
  if (wg == 0) asm volatile("bar.sync 6, 256;" ::: "memory");
  STAMP(2 + wg);

  Ring ring{0, 0};
  const uint64_t desc0 = bdesc(sb);
#pragma unroll 1
  for (int step = 0; step < 12; step++) {
    float acc[64];
    uint32_t prev = 0;
#pragma unroll
    for (int kb = 0; kb < 9; kb++) {
      mbar_wait(sb + B_FULL + 8 * ring.slot, ring.phase);
      const uint64_t db = desc0 + (ring.off() >> 4);
      if (LAG1 == LAG2) {
        if (kb == 9 - LAG1) lag_sync(wg);
      } else {
        if (kb == 9 - LAG1 && step < 9) lag_sync(wg);
        if (kb == 9 - LAG2 && step >= 9) lag_sync(wg);
      }
      WG_FENCE();
#pragma unroll
      for (int k = 0; k < 4; k++) wgmma_rs<128, 1>(acc, &A[(kb * 4 + k) * 4], db + k * 128, kb + k);
      WG_COMMIT();
      if (kb == 8) lag_arrive(wg);
      if (kb > 0) {
        WG_WAIT(1);
        release_slot(sb, prev, lane);
      }
      prev = ring.slot;
      ring.next();
    }
    if (step > 9) {
      mbar_wait(sb + B_XIN + 8 * (wg * 4 + step - 10), 0);
      mbar_wait(sb + B_SE + 8 * (wg * 3 + step - 10), 0);
    }
    WG_WAIT(0);
    release_slot(sb, prev, lane);
    if (step == 0) wg_bar(wg);
    if (step < 9) {
      uint32_t hp[16];
      const float c0 = 0.5f * rs0, c1 = 0.5f * rs1;
#pragma unroll
      for (int i = 0; i < 16; i++) {
        const float c = (i & 1) ? c1 : c0;
        const float g0 = acc[2 * i] * c, g1 = acc[2 * i + 1] * c;
        const float h0 = fmaf(g0, tanh_hw(g0), g0) * acc[32 + 2 * i];
        const float h1 = fmaf(g1, tanh_hw(g1), g1) * acc[33 + 2 * i];
        hp[i] = pack_bf16(h0, h1);
      }
      if (step < 8) {
#pragma unroll
        for (int j = 0; j < 4; j++) sts128(priv + step * BOX + j * 512, &hp[4 * j]);
      } else {
#pragma unroll
        for (int i = 0; i < 16; i++) A[128 + i] = hp[i];
#pragma unroll
        for (int c = 0; c < 8; c++)
#pragma unroll
          for (int j = 0; j < 4; j++) lds128(&A[16 * c + 4 * j], priv + c * BOX + j * 512);
        STAMP(4 + wg);
      }
    } else {
      const int e = step - 9;
      stage_partial(acc, priv + (2 + (e & 1)) * BOX);
      if (e > 0) add_partial(acc + 32, priv + ((e - 1) & 1) * BOX);
      stage_partial(acc + 32, priv + 4 * BOX);
      stage_done(sb + B_SF + 8 * (wg * 5 + e), lane);
    }
  }
  STAMP(6 + wg);

  float acc[32], sum[32];
  {
    uint2 p8[8];
    uint32_t res[4];
    const int t = fresh_tid();
    const int col = 512 + 16 * (t >> 6) + 8 * (t & 1) + 2 * ((t >> 1) & 3), row = (s >> 2) * 1024 + r * 64 + (s & 3) * 16 + ((t >> 3) & 7);
    step64<0>(acc, A, sb, desc0, ring, wg, lane, [&](int st) {
      if (st == 0) {
        mbar_wait(sb + B_B8, 0);
        const uint2* src = reinterpret_cast<const uint2*>(&g->part8[r * 8 * 1024 + s * 128]) + t;
#pragma unroll
        for (int i = 0; i < 8; i++) p8[i] = __ldcg(src + i * 2048);
        const unsigned short* hp = reinterpret_cast<const unsigned short*>(g->hT) + col * L + row;
#pragma unroll
        for (int i = 0; i < 4; i++) res[i] = __ldcg(hp + (i & 1) * L + (i >> 1) * 8);
      } else if (st == 3) {
        float v[4] = {0.f, 0.f, 0.f, 0.f};
#pragma unroll
        for (int i = 0; i < 8; i++) {
          v[0] += bf_lo(p8[i].x); v[1] += bf_hi(p8[i].x);
          v[2] += bf_lo(p8[i].y); v[3] += bf_hi(p8[i].y);
        }
        const uint32_t ra = sb + OFF_MISC + 160 + ((t >> 1) & 28);
        const float r0 = __uint_as_float(lds32(ra)), r1 = __uint_as_float(lds32(ra + 32));
        *reinterpret_cast<uint32_t*>(out + row * D + col) = pack_bf16(fmaf(v[0], r0, bf_lo(res[0])), fmaf(v[1], r0, bf_lo(res[1])));
        *reinterpret_cast<uint32_t*>(out + (row + 8) * D + col) =
            pack_bf16(fmaf(v[2], r1, bf_lo(res[2])), fmaf(v[3], r1, bf_lo(res[3])));
        mbar_wait(sb + B_SE + 8 * (wg * 3 + 2), 0);
      } else if (st == 4) {
        mbar_wait(sb + B_XIN + 8 * (wg * 4 + 2), 0);
        load_partial(sum, priv);
      }
    });
#pragma unroll
    for (int i = 0; i < 32; i++) acc[i] += sum[i];
    stage_partial(acc, priv + 4 * BOX);
    stage_done(sb + B_SF + 8 * (wg * 5 + 3), lane);
    STAMPC(tid == 0, 12);
  }
  step64<1>(acc, A, sb, desc0, ring, wg, lane, [&](int st) {});
  stage_partial(acc, priv + 3 * BOX);
  stage_done(sb + B_SF + 8 * (wg * 5 + 4), lane);
  STAMPC(tid == 0, 13);
  step64<2>(acc, A, sb, desc0, ring, wg, lane, [&](int st) {
    if (st == 1) {
      mbar_wait(sb + B_LIN + 8 * (wg * 2), 0);
#pragma unroll
      for (int k = 0; k < 4; k++) {
        uint32_t v[4];
        ldsm4t(v, sb + stash + 7 * BOX + tr_off + k * 2048);
#pragma unroll
        for (int i = 0; i < 4; i++) {
          sum[8 * k + 2 * i] = bf_lo(v[i]);
          sum[8 * k + 2 * i + 1] = bf_hi(v[i]);
        }
      }
    } else if (st == 4) {
      mbar_wait(sb + B_XIN + 8 * (wg * 4 + 3), 0);
      mbar_wait(sb + B_LIN + 8 * (wg * 2 + 1), 0);
#pragma unroll
      for (int j = 0; j < 4; j++) {
        uint32_t v[4][4];
        lds128(v[0], priv + 5 * BOX + j * 512);
        lds128(v[1], priv + BOX + j * 512);
        lds128(v[2], priv + 6 * BOX + j * 512);
        lds128(v[3], priv + j * 512);
#pragma unroll
        for (int i = 0; i < 4; i++) {
          const uint32_t p = add_bf16x2(add_bf16x2(v[0][i], v[1][i]), add_bf16x2(v[2][i], v[3][i]));
          sum[8 * j + 2 * i] = fmaf(bf_lo(p), (i & 1) ? rs1 : rs0, sum[8 * j + 2 * i]);
          sum[8 * j + 2 * i + 1] = fmaf(bf_hi(p), (i & 1) ? rs1 : rs0, sum[8 * j + 2 * i + 1]);
          asm volatile("" : "+f"(sum[8 * j + 2 * i]), "+f"(sum[8 * j + 2 * i + 1]));
        }
      }
    }
  });
  STAMP(8 + wg);
  const uint32_t ob = sb + stash + 5 * BOX + w * 2048;
  __syncwarp();
#pragma unroll
  for (int i = 0; i < 4; i++) {
    uint32_t p[4];
#pragma unroll
    for (int j = 0; j < 4; j++) {
      const float rr = (j & 1) ? rs1 : rs0;
      p[j] = pack_bf16(fmaf(acc[8 * i + 2 * j], rr, sum[8 * i + 2 * j]), fmaf(acc[8 * i + 2 * j + 1], rr, sum[8 * i + 2 * j + 1]));
    }
    stsm4(ob + (lane & 15) * 128 + (((2 * i + (lane >> 4)) ^ (lane & 7)) << 4), p);
  }
  __syncwarp();
  __nv_bfloat16* o = out + (wg * 1024 + r * 64 + w * 16 + (lane >> 3)) * D + s * 64 + (lane & 7) * 8;
#pragma unroll
  for (int i = 0; i < 4; i++) {
    const int row = 4 * i + (lane >> 3);
    uint32_t v[4];
    lds128(v, ob + row * 128 + (((lane & 7) ^ (row & 7)) << 4));
    *reinterpret_cast<uint4*>(o + 4 * i * D) = make_uint4(v[0], v[1], v[2], v[3]);
  }
  STAMP(10 + wg);
}

__device__ __forceinline__ void load_stage(uint32_t sb, const Ring& ring, int it, int s, const CUtensorMap* w1,
                                           const CUtensorMap* w3, const CUtensorMap* w2) {
  const uint32_t bar = sb + B_FULL + 8 * ring.slot, dst = sb + ring.off();
  if (it < 81) {
    const int step = it / 9, kb = it - step * 9;
    mbar_expect(bar, SLOT);
    tma2d(dst, w1, s * 576 + step * 64, kb * 64, bar);
    tma2d(dst + BOX, w3, s * 576 + step * 64, kb * 64, bar);
  } else if (it < 108) {
    const int e = (it - 81) / 9, kb = it - 81 - e * 9;
    mbar_expect(bar, SLOT);
    tma2d(dst, w2, (((s + 2 * e + 2) & 7) ^ 1) * 64, s * 576 + kb * 64, bar);
    tma2d(dst + BOX, w2, (e == 0 ? 8 : (s + 2 * e) & 7) * 64, s * 576 + kb * 64, bar);
  } else {
    const int e = (it - 108) / 5, st = it - 108 - e * 5;
    const int blk = e == 0 ? (s + 6) & 7 : e == 1 ? s ^ 1 : s;
    mbar_expect(bar, st < 4 ? SLOT : BOX);
    tma2d(dst, w2, blk * 64, s * 576 + st * 128, bar);
    if (st < 4) tma2d(dst + BOX, w2, blk * 64, s * 576 + st * 128 + 64, bar);
  }
}

__device__ __forceinline__ void ffn_producer(uint32_t sb, int s, int first, const CUtensorMap* w1, const CUtensorMap* w3,
                                             const CUtensorMap* w2) {
  Ring ring{(uint32_t)first, 1};
  mbar_wait(sb + B_CV + 8, 0);
#pragma unroll 1
  for (int it = first; it < 123; it++) {
    mbar_wait(sb + B_EMPTY + 8 * ring.slot, ring.slot == NS - 1 ? ring.phase ^ 1 : ring.phase);
    if (elect_one()) load_stage(sb, ring, it, s, w1, w3, w2);
    __syncwarp();
    ring.next();
  }
  const uint32_t pb = mapa(sb, (s & 1) ^ 1);
#pragma unroll 1
  for (int wg = 0; wg < 2; wg++) {
    const uint32_t stash = OFF_STASH + wg * STASH_STRIDE;
    mbar_wait(sb + B_SF + 8 * (wg * 5 + 4), 0);
    if (elect_one()) bulk_peer(pb + stash + BOX, sb + stash + 3 * BOX, BOX, pb + B_XIN + 8 * (wg * 4 + 3));
    __syncwarp();
  }
}

__device__ __forceinline__ void ffn_sender(uint32_t sb, Scratch* g, int r, int s, int wg) {
  const uint32_t stash = OFF_STASH + wg * STASH_STRIDE, pb = mapa(sb, (s & 1) ^ 1);
  mbar_wait(sb + B_CV + 8 * wg, 0);
  STAMPC(1, 58 + wg);
  if (elect_one()) {
    asm volatile("fence.acq_rel.gpu;" ::: "memory");
    red_add(&g->epoch[32 * wg], 1);
  }
  __syncwarp();
#pragma unroll 1
  for (int e = 0; e < 4; e++) {
    mbar_wait(sb + B_SF + 8 * (wg * 5 + e), 0);
    STAMPC(e == 3 && wg == 0, 62);
    if (e == 0) {
      if (elect_one()) mbar_arrive_cluster(pb + B_PRDY + 8 * wg);
      __syncwarp();
      mbar_wait(sb + B_PRDY + 8 * wg, 0);
    }
    if (elect_one()) {
      if (e < 3) bulk_peer(pb + stash + (e & 1) * BOX, sb + stash + (2 + (e & 1)) * BOX, BOX, pb + B_XIN + 8 * (wg * 4 + e));
      const int idx = ((r * 8 + ((s + 2 * e) & 7)) * 3 + e - 1) * 2 + wg;
      uint4* dst = e == 0 ? &g->part8[((r * 8 + s) * 2 + wg) * 512] : &g->part[idx * 512];
#pragma unroll 1
      for (uint32_t q = 0, n = e == 3 ? BOX : PACE; q < BOX; q += n) {
        bulk_store(dst + (q >> 4), sb + stash + 4 * BOX + q, n);
        asm volatile("cp.async.bulk.commit_group;" ::: "memory");
        asm volatile("cp.async.bulk.wait_group.read 0;" ::: "memory");
      }
      if (e < 3) mbar_arrive(sb + B_SE + 8 * (wg * 3 + e));
      if (e != 2) {
        asm volatile("cp.async.bulk.wait_group 0;" ::: "memory");
        STAMPC(e == 3 && wg == 0, 63);
        asm volatile("fence.acq_rel.gpu;" ::: "memory");
        if (e == 0) {
#pragma unroll
          for (int q = 0; q < 4; q++) red_add(&g->flag8[r * 8 + wg * 4 + q], 1);
        } else {
          if (e == 3) red_add(&g->flag[((r * 8 + ((s + 4) & 7)) * 3 + 1) * 2 + wg], 1);
          red_add(&g->flag[idx], 1);
        }
        STAMPC(e == 3, 28 + wg);
      }
    }
    __syncwarp();
  }
  mbar_wait(sb + B_XIN + 8 * (wg * 4 + 3), 0);
  if (elect_one()) mbar_arrive_cluster(pb + B_DONE + 8 * wg);
  __syncwarp();
  mbar_wait(sb + B_DONE + 8 * wg, 0);
}

__device__ __forceinline__ void ffn_receiver(uint32_t sb, Scratch* g, int c, int r, int s, const CUtensorMap* ht,
                                             const CUtensorMap* ht3) {
  const int lane = fresh_tid() & 31;
#pragma unroll 1
  for (int h = 0; h < 2; h++) {
    wait_flag(&g->epoch[32 * h], (lds32(sb + OFF_MISC) & ~127u) + 128);
    STAMPC(lane == 0 && h == 0, 31);
    mbar_wait(sb + B_CV + 8, 0);
    STAMPC(lane == 0, h ? 23 : 1);
    if (elect_one()) {
      asm volatile("fence.proxy.async.global;" ::: "memory");
      tma2d(sb + (NS - 1) * SLOT + h * BOX, ht, h * 1024 + r * 64, 0, sb + B_H + 40 * h);
#pragma unroll
      for (int i = 0; i < 4; i++)
        tma2d(sb + OFF_STASH + h * STASH_STRIDE + i * SLOT, ht3, h * 1024 + r * 64, 64 + 128 * i, sb + B_H + 40 * h + 8 + 8 * i);
    }
    __syncwarp();
  }
  if (lane < 6) g->stats[(lane >> 1) * 256 + 2 * c + (lane & 1)] = make_uint4(0, 0, 0, 0);
#pragma unroll 1
  for (int wg = 0; wg < 2; wg++) {
    mbar_wait(sb + B_SF + 8 * (wg * 5), 0);
    if (elect_one()) tma2d(sb + OFF_STASH + wg * STASH_STRIDE + 7 * BOX, ht, wg * 1024 + r * 64, s * 64, sb + B_LIN + 8 * (wg * 2));
    __syncwarp();
  }
  wait_flag(&g->flag8[r * 8 + s], 8);
  __syncwarp();
  if (lane == 0) {
    g->flag8[r * 8 + s] = 0;
    mbar_arrive(sb + B_B8);
  }
  uint32_t todo = 0x3f;
  const int base = (r * 8 + s) * 6;
#pragma unroll 1
  for (uint32_t spins = 0; todo; spins++) {
    if (spins > SPIN_LIMIT) __trap();
    uint32_t ready = __ballot_sync(~0u, ((todo >> lane) & 1) && ld_acquire(&g->flag[base + lane]) != 0);
    __syncwarp();
    todo &= ~ready;
#pragma unroll 1
    for (; ready; ready &= ready - 1) {
      const int i = __ffs(ready) - 1, wg = i & 1, j = i >> 1;
      if (j == 2) mbar_wait(sb + B_SF + 8 * (wg * 5 + 3), 0);
      if (elect_one()) {
        asm volatile("fence.proxy.async.global;" ::: "memory");
        bulk_load(sb + OFF_STASH + wg * STASH_STRIDE + (j == 2 ? 0 : 5 + j) * BOX, &g->part[(base + i) * 512], BOX,
                  sb + B_LIN + 8 * (wg * 2 + (j > 0)));
      }
      __syncwarp();
    }
  }
  if (lane < 6) g->flag[base + lane] = 0;
  STAMPC(lane == 0, 30);
}

__global__ void __launch_bounds__(384, 1)
fused_kernel(const __grid_constant__ SsmParams p, __nv_bfloat16* __restrict__ out,
             const __grid_constant__ CUtensorMap tm_w1, const __grid_constant__ CUtensorMap tm_w3,
             const __grid_constant__ CUtensorMap tm_w2, const __grid_constant__ CUtensorMap tm_ht,
             const __grid_constant__ CUtensorMap tm_ht3, const __grid_constant__ CUtensorMap tm_x) {
  extern __shared__ __align__(1024) uint8_t smem[];
  uint32_t sb = (uint32_t)__cvta_generic_to_shared(smem);
  asm volatile("" : "+r"(sb));
  const int c = blockIdx.x, cl = c >> 1, rank = c & 1, tid = threadIdx.x, warp = warp_index(), wg = warp >> 2;
  const int s = ((cl & 1) * 2 + ((cl >> 3) & 1)) * 2 + rank, r = ((cl >> 1) & 3) * 4 + (cl >> 4);
  STAMPC(tid == 0, 0);
  Scratch* const g = p.g;
  unsigned target = 0;
  int first = 0;
  const int w = warp & 3, lane = tid & 31;
  const int ch0 = 9 * cl + 5 * rank;
  ModeIn in;
  uint4 xv[9];
  uint32_t t0;
  asm volatile("mov.u32 %0, %clock;" : "=r"(t0));
  if (wg < 2) {
    in = load_modes(p, ch0 + (warp >> 1), tid & 63);
  } else {
    const uint4* xr = reinterpret_cast<const uint4*>(p.x) + (16 * c + ((tid & 127) >> 3)) * (D / 8) + (tid & 7);
    for (uint32_t now = t0; now - t0 < XDELAY;) asm volatile("mov.u32 %0, %clock;" : "=r"(now));
#pragma unroll
    for (int i = 0; i < 9; i++)
      asm volatile("ld.global.nc.v4.u32 {%0,%1,%2,%3}, [%4];"
                   : "=r"(xv[i].x), "=r"(xv[i].y), "=r"(xv[i].z), "=r"(xv[i].w) : "l"(xr + 8 * i));
    if (rank == 1) in = load_modes(p, ch0 - 1, tid & 63);
  }
  const uint32_t dsk = ldg16(p.dskip + min(ch0 + (tid & 7), D - 1));
  STAMP(38 + wg);
  if (warp == 9) {
    const uint32_t z[4] = {0, 0, 0, 0};
#pragma unroll 1
    for (int i = 0; i < 5; i++)
    {
      if (lane < 26) sts128(sb + (lane < 24 ? OFF_U + i * U_PITCH : OFF_PK - 384 + i * PK_PITCH) + lane * 16, z);
    }
  }
  if (warp == 8 && elect_one()) {
    asm volatile("prefetch.tensormap [%0];" ::"l"(&tm_x) : "memory");
#pragma unroll
    for (uint32_t b = B_G; b < B_END; b += 8) mbar_init(sb + b, b == B_UX ? 2 : b < B_SF ? 1 : b < B_EMPTY ? 4 : 8);
#pragma unroll
    for (uint32_t b = B_G; b < B_FULL; b += 8)
      mbar_expect(sb + b, b < B_PK ? 2 * BOX : b < B_LIN ? BOX : b < B_H ? 2 * BOX : b < B_UX ? ((b - B_H) % 40 ? 2 : 1) * BOX : 5 * L);
    asm volatile("fence.mbarrier_init.release.cluster;" ::: "memory");
    for (uint32_t now = t0; now - t0 < GDELAY;) asm volatile("mov.u32 %0, %clock;" : "=r"(now));
#pragma unroll
    for (int i = 0; i < 2; i++)
      asm volatile(
          "cp.async.bulk.tensor.5d.shared::cluster.global.mbarrier::complete_tx::bytes [%0], [%1, {%3, %4, %4, %4, %5}], [%2];"
          ::"r"(sb + OFF_G + i * SLOT), "l"(&tm_x), "r"(sb + B_G + 8 * i), "r"((9 * cl) & ~7), "r"(0), "r"(32 * rank + 16 * i)
          : "memory");
  }
  __syncwarp();
  asm volatile("barrier.cluster.arrive.relaxed.aligned;" ::: "memory");
  STAMPC(tid == 256, 41);
  if (wg == 2) {
    ln1_stats(sb, g, c, xv);
    STAMP(14);
    asm volatile("barrier.cluster.wait.aligned;" ::: "memory");
    x_transpose(sb, c, w);
    STAMP(18);
  }
  const int ntask = wg < 2 ? 2 : 1 - rank;
  if (wg < 2 || rank == 1) {
    float acc[6][4];
#pragma unroll
    for (int i = 0; i < 6; i++) acc[i][0] = acc[i][1] = acc[i][2] = acc[i][3] = 0.f;
#pragma unroll 1
    for (int k = wg >> 1; k < 2; k++) {
      kgen_modes(sb + OFF_WS + wg * WS_BYTES + w * WS_WARP, in, (wg == 2 ? w >> 1 : k) ? 0x3244 : 0x1044, acc);
      STAMP(46 + wg * 2 + k);
    }
    uint32_t st[12];
    if (wg < 2) asm volatile("barrier.cluster.wait.aligned;" ::: "memory");
    kgen_finish(sb, g, wg, acc, st);
    STAMP(52 + wg);
    if (wg < 2) {
      if (tid < 8) sts32(sb + OFF_MISC + 128 + 4 * tid, dsk * 0x10001u);
      ln1_apply(sb, g, st);
      asm volatile("fence.proxy.async.shared::cta;\nbar.arrive 6, 384;\nbar.sync 4, 256;" ::: "memory");
    } else {
      asm volatile("fence.proxy.async.shared::cta;" ::: "memory");
      wg_bar(2);
      if (w == 2 && elect_one()) {
        const uint32_t pb = mapa(sb, 0), off = OFF_PK + 4 * PK_PITCH + 32;
        bulk_peer(pb + off, sb + off, BOX, pb + B_PK);
      }
      __syncwarp();
    }
  }
  if (wg == 2) {
    asm volatile("bar.sync 6, 384;" ::: "memory");
    mbar_wait(sb + B_UX, 0);
    if (w == 0 && elect_one()) {
#pragma unroll 1
      for (int i = 0; i < EARLY; i++) {
        const uint32_t bar = sb + B_FULL + 8 * i, dst = sb + i * SLOT;
        mbar_expect(bar, SLOT);
        tma2d(dst, &tm_w1, s * 576, i * 64, bar);
        tma2d(dst + BOX, &tm_w3, s * 576, i * 64, bar);
      }
      asm volatile("prefetch.tensormap [%0];" ::"l"(&tm_ht) : "memory");
      asm volatile("prefetch.tensormap [%0];" ::"l"(&tm_ht3) : "memory");
    }
    if (w == 1 && lane < 9) {
      const __nv_bfloat16* wp = (lane < 3 ? p.w1 : lane < 6 ? p.w3 : p.w2) + c * 20736 + (lane % 3) * 6912;
      asm volatile("cp.async.bulk.prefetch.L2.global [%0], %1;" ::"l"(wp), "r"(13824) : "memory");
    }
    __syncwarp();
    if (w == 3) {
      asm volatile("ld.relaxed.gpu.global.u32 %0, [%1];" : "=r"(target) : "l"(&g->epoch[32]) : "memory");
      sts32(sb + OFF_MISC, target);
    }
    if (rank == 0) mbar_wait(sb + B_PK, 0);
    STAMP(55);
  }
  first = EARLY;
  STAMPC(tid == 0, 19);
#pragma unroll 1
  for (int local = 2 * wg; local < 2 * wg + ntask; local++)
    conv_task(sb, g, wg, w, local, ch0 + local);
  STAMP(20 + wg);
  asm volatile("fence.proxy.async.shared::cta;" ::: "memory");
  __syncwarp();
  if (wg == 2) wg_bar(2);
  else if (elect_one()) mbar_arrive(sb + B_CV + 8);
  __syncwarp();

  if (wg < 2) {
    asm volatile("setmaxnreg.inc.sync.aligned.u32 240;");
    ffn_consumer(sb, g, warp, r, s, out);
  } else {
    asm volatile("setmaxnreg.dec.sync.aligned.u32 24;");
    const int hw = warp & 3;
    if (hw == 0) ffn_producer(sb, s, first, &tm_w1, &tm_w3, &tm_w2);
    else if (hw < 3) ffn_sender(sb, g, r, s, hw - 1);
    else ffn_receiver(sb, g, c, r, s, &tm_ht, &tm_ht3);
  }
}

typedef CUresult (*EncodeFn)(CUtensorMap*, CUtensorMapDataType, cuuint32_t, void*, const cuuint64_t*, const cuuint64_t*,
                             const cuuint32_t*, const cuuint32_t*, CUtensorMapInterleave, CUtensorMapSwizzle,
                             CUtensorMapL2promotion, CUtensorMapFloatOOBfill);

void make_map(EncodeFn enc, CUtensorMap* m, void* p, uint64_t cols, uint64_t rows, uint32_t box_rows = 64) {
  cuuint64_t dims[2] = {cols, rows}, strides[1] = {cols * 2};
  cuuint32_t box[2] = {64, box_rows}, es[2] = {1, 1};
  enc(m, CU_TENSOR_MAP_DATA_TYPE_BFLOAT16, 2, p, dims, strides, box, es, CU_TENSOR_MAP_INTERLEAVE_NONE,
      CU_TENSOR_MAP_SWIZZLE_128B, CU_TENSOR_MAP_L2_PROMOTION_L2_128B, CU_TENSOR_MAP_FLOAT_OOB_FILL_NONE);
}

}

extern "C" void kernel_launch(void* const* d_in, const int* in_sizes, int n_in, void* d_out, int out_size) {
  typedef const __nv_bfloat16* P;
  void* fn = nullptr;
  cudaDriverEntryPointQueryResult qr;
  cudaGetDriverEntryPoint("cuTensorMapEncodeTiled", &fn, cudaEnableDefault, &qr);
  EncodeFn enc = (EncodeFn)fn;
  void* hT = nullptr;
  cudaGetSymbolAddress(&hT, g_scratch);
  CUtensorMap m1, m3, m2, mh, mh3, mx;
  make_map(enc, &m1, d_in[10], F, D);
  make_map(enc, &m3, d_in[11], F, D);
  make_map(enc, &m2, d_in[12], D, F);
  make_map(enc, &mh, hT, L, D);
  make_map(enc, &mh3, hT, L, D, 128);
  {
    cuuint64_t dims[5] = {D, 2, 4, 4, 64}, strides[4] = {D * 2, D * 16, D * 4, D * 64};
    cuuint32_t box[5] = {16, 2, 4, 4, 16}, es[5] = {1, 1, 1, 1, 1};
    enc(&mx, CU_TENSOR_MAP_DATA_TYPE_BFLOAT16, 5, d_in[0], dims, strides, box, es, CU_TENSOR_MAP_INTERLEAVE_NONE,
        CU_TENSOR_MAP_SWIZZLE_32B, CU_TENSOR_MAP_L2_PROMOTION_L2_128B, CU_TENSOR_MAP_FLOAT_OOB_FILL_NONE);
  }
  SsmParams p = {(P)d_in[0], (P)d_in[1], (P)d_in[2], (P)d_in[3], (P)d_in[4], (P)d_in[5],
                 (P)d_in[6], (P)d_in[7], (P)d_in[8], (P)d_in[10], (P)d_in[11], (P)d_in[12], (Scratch*)hT};
  cudaFuncSetAttribute(fused_kernel, cudaFuncAttributeMaxDynamicSharedMemorySize, SMEM_BYTES);
  cudaLaunchConfig_t cfg = {};
  cfg.gridDim = dim3(128);
  cfg.blockDim = dim3(384);
  cfg.dynamicSmemBytes = SMEM_BYTES;
  cfg.stream = cudaStreamPerThread;
  cudaLaunchAttribute at[1];
  at[0].id = cudaLaunchAttributeClusterDimension;
  at[0].val.clusterDim.x = 2;
  at[0].val.clusterDim.y = 1;
  at[0].val.clusterDim.z = 1;
  cfg.attrs = at;
  cfg.numAttrs = 1;
  cudaLaunchKernelEx(&cfg, fused_kernel, p, (__nv_bfloat16*)d_out, m1, m3, m2, mh, mh3, mx);
}
```

```cpp
#include <cuda_runtime.h>
#include <cuda_bf16.h>
#include <cuda.h>
#include <stdint.h>

#define LAG1 4
#define LAG2 4
#define LAG3 3
#define HMC 0
#define GDELAY 1900
#define XDELAY 900
#define XST 4
#define B8ST 1
#define PACE 4096

namespace {

constexpr int L = 2048, D = 576, F = 4608, NMODE = 128;
constexpr int NS = 6;
constexpr uint32_t SLOT = 16384, BOX = 8192;
constexpr uint32_t OFF_STASH = NS * SLOT, STASH_STRIDE = 8 * BOX;
constexpr uint32_t OFF_BAR = NS * SLOT + 16 * BOX;
constexpr uint32_t B_G = OFF_BAR, B_PK = B_G + 8 * 2, B_XIN = B_PK + 8, B_LIN = B_XIN + 8 * 8, B_H = B_LIN + 8 * 4, B_UX = B_H + 8 * 10,
                   B_VAR = B_UX + 8, B_B8 = B_VAR + 16, B_FULL = B_B8 + 8, B_SE = B_FULL + 8 * NS, B_PRDY = B_SE + 8 * 6,
                   B_DONE = B_PRDY + 8 * 2, B_SF = B_DONE + 8 * 2, B_EMPTY = B_SF + 8 * 10, B_CV = B_EMPTY + 8 * NS, B_END = B_CV + 8 * 3;
constexpr uint32_t OFF_MISC = OFF_BAR + 768;
constexpr uint32_t OFF_ZERO = OFF_MISC + 224;
constexpr uint32_t OFF_VAR = OFF_BAR + 1536;
constexpr uint32_t SMEM_BYTES = OFF_VAR + 512;
constexpr uint32_t SPIN_LIMIT = 1u << 24;
static_assert(B_END <= OFF_BAR + 512, "barrier region");

constexpr uint32_t EARLY = 4;
constexpr uint32_t OFF_G = 0;
constexpr uint32_t OFF_WS = 2 * SLOT, WS_WARP = 7168, WS_KC = 4 * WS_WARP + 16, KC_PITCH = 1312, WS_BYTES = 32768;
constexpr uint32_t OFF_PART = EARLY * SLOT;
constexpr uint32_t OFF_U = OFF_WS + 3 * WS_BYTES, U_PAD = 384, U_PITCH = U_PAD + 4096;
constexpr uint32_t OFF_X = OFF_U + 5 * U_PITCH, X_PITCH = 4160;
constexpr uint32_t OFF_PK = OFF_X + 5 * X_PITCH, PK_PITCH = 8224;
constexpr uint32_t OFF_STG = OFF_PK + 5 * PK_PITCH, STG_PITCH = 2112;
static_assert(OFF_STG + 5 * STG_PITCH <= OFF_BAR, "front region");
static_assert(WS_KC + 2 * KC_PITCH <= WS_BYTES, "scratch");

struct Scratch {
  __nv_bfloat16 hT[D * L];
  uint4 part[16 * 8 * 3 * 2 * 512];
  uint4 part8[16 * 8 * 2 * 512];
  uint4 stats[3 * 256];
  unsigned flag[16 * 8 * 3 * 2];
  unsigned flag8[16 * 8];
  unsigned epoch[64];
};
__device__ __align__(1024) Scratch g_scratch;
#define STAMP(i)
#define STAMPC(c, i)

__device__ __forceinline__ int fresh_tid() {
  int t;
  asm volatile("mov.u32 %0, %tid.x;" : "=r"(t));
  return t;
}
__device__ __forceinline__ int warp_index() { return __shfl_sync(~0u, fresh_tid() >> 5, 0); }
__device__ __forceinline__ void mbar_init(uint32_t b, uint32_t c) {
  asm volatile("mbarrier.init.shared::cta.b64 [%0], %1;" ::"r"(b), "r"(c));
}
__device__ __forceinline__ void mbar_expect(uint32_t b, uint32_t n) {
  asm volatile("mbarrier.arrive.expect_tx.shared::cta.b64 _, [%0], %1;" ::"r"(b), "r"(n) : "memory");
}
__device__ __forceinline__ void mbar_arrive(uint32_t b) {
  asm volatile("mbarrier.arrive.shared::cta.b64 _, [%0];" ::"r"(b) : "memory");
}
__device__ __forceinline__ void mbar_arrive_cluster(uint32_t b) {
  asm volatile("mbarrier.arrive.shared::cluster.b64 _, [%0];" ::"r"(b) : "memory");
}
__device__ __forceinline__ void mbar_wait(uint32_t b, uint32_t parity) {
  asm volatile(
      "{\n.reg .pred p;\n.reg .u32 c;\nmov.u32 c, 0;\n"
      "WAIT:\nmbarrier.try_wait.parity.shared::cta.b64 p, [%0], %1;\n@p bra DONE;\n"
      "add.u32 c, c, 1;\nsetp.lt.u32 p, c, %2;\n@p bra WAIT;\ntrap;\nDONE:\n}\n" ::"r"(b), "r"(parity), "n"(SPIN_LIMIT) : "memory");
}
__device__ __forceinline__ bool elect_one() {
  uint32_t p;
  asm volatile("{\n.reg .pred p;\nelect.sync _|p, 0xffffffff;\nselp.u32 %0, 1, 0, p;\n}\n" : "=r"(p));
  return p != 0;
}
__device__ __forceinline__ void tma2d(uint32_t dst, const CUtensorMap* m, int c0, int c1, uint32_t bar) {
  asm volatile("cp.async.bulk.tensor.2d.shared::cluster.global.mbarrier::complete_tx::bytes [%0], [%1, {%3, %4}], [%2];"
               ::"r"(dst), "l"(m), "r"(bar), "r"(c0), "r"(c1) : "memory");
}
__device__ __forceinline__ void tma2d_mc(uint32_t dst, const CUtensorMap* m, int c0, int c1, uint32_t bar) {
  asm volatile(
      "cp.async.bulk.tensor.2d.shared::cluster.global.mbarrier::complete_tx::bytes.multicast::cluster [%0], [%1, {%3, %4}], [%2], %5;"
      ::"r"(dst), "l"(m), "r"(bar), "r"(c0), "r"(c1), "h"((uint16_t)3) : "memory");
}
__device__ __forceinline__ void bulk_load(uint32_t dst, const void* src, uint32_t bytes, uint32_t bar) {
  asm volatile("cp.async.bulk.shared::cluster.global.mbarrier::complete_tx::bytes [%0], [%1], %2, [%3];"
               ::"r"(dst), "l"(src), "r"(bytes), "r"(bar) : "memory");
}
__device__ __forceinline__ void bulk_store(void* dst, uint32_t src, uint32_t bytes) {
  asm volatile("cp.async.bulk.global.shared::cta.bulk_group [%0], [%1], %2;" ::"l"(dst), "r"(src), "r"(bytes) : "memory");
}
__device__ __forceinline__ void ldsm4t(uint32_t* r, uint32_t a) {
  asm volatile("ldmatrix.sync.aligned.m8n8.x4.trans.shared.b16 {%0,%1,%2,%3}, [%4];"
               : "=r"(r[0]), "=r"(r[1]), "=r"(r[2]), "=r"(r[3]) : "r"(a) : "memory");
}
__device__ __forceinline__ void ldsm4(uint32_t* r, uint32_t a) {
  asm volatile("ldmatrix.sync.aligned.m8n8.x4.shared.b16 {%0,%1,%2,%3}, [%4];"
               : "=r"(r[0]), "=r"(r[1]), "=r"(r[2]), "=r"(r[3]) : "r"(a) : "memory");
}
__device__ __forceinline__ void ldsm2t(uint32_t* r, uint32_t a) {
  asm volatile("ldmatrix.sync.aligned.m8n8.x2.trans.shared.b16 {%0,%1}, [%2];" : "=r"(r[0]), "=r"(r[1]) : "r"(a) : "memory");
}
__device__ __forceinline__ void st_async128(uint32_t a, const uint32_t* r, uint32_t bar) {
  asm volatile("st.async.weak.shared::cluster.mbarrier::complete_tx::bytes.v4.b32 [%0], {%1,%2,%3,%4}, [%5];"
               ::"r"(a), "r"(r[0]), "r"(r[1]), "r"(r[2]), "r"(r[3]), "r"(bar) : "memory");
}
__device__ __forceinline__ void ldsm2(uint32_t* r, uint32_t a) {
  asm volatile("ldmatrix.sync.aligned.m8n8.x2.shared.b16 {%0,%1}, [%2];" : "=r"(r[0]), "=r"(r[1]) : "r"(a) : "memory");
}
__device__ __forceinline__ void ldsm1(uint32_t* r, uint32_t a) {
  asm volatile("ldmatrix.sync.aligned.m8n8.x1.shared.b16 {%0}, [%1];" : "=r"(r[0]) : "r"(a) : "memory");
}
__device__ __forceinline__ void ldc128(uint32_t* r, uint32_t a) {
  asm volatile("ld.shared::cluster.v4.b32 {%0,%1,%2,%3}, [%4];" : "=r"(r[0]), "=r"(r[1]), "=r"(r[2]), "=r"(r[3]) : "r"(a) : "memory");
}
__device__ __forceinline__ void bulk_peer(uint32_t dst, uint32_t src, uint32_t bytes, uint32_t bar) {
  asm volatile("cp.async.bulk.shared::cluster.shared::cta.mbarrier::complete_tx::bytes [%0], [%1], %2, [%3];"
               ::"r"(dst), "r"(src), "r"(bytes), "r"(bar) : "memory");
}
__device__ __forceinline__ uint32_t mapa(uint32_t a, uint32_t rank) {
  uint32_t r;
  asm("mapa.shared::cluster.u32 %0, %1, %2;" : "=r"(r) : "r"(a), "r"(rank));
  return r;
}
__device__ __forceinline__ uint32_t lds32(uint32_t a) {
  uint32_t r;
  asm volatile("ld.shared.b32 %0, [%1];" : "=r"(r) : "r"(a) : "memory");
  return r;
}
__device__ __forceinline__ uint32_t lds16(uint32_t a) {
  uint32_t r;
  asm volatile("ld.shared.u16 %0, [%1];" : "=r"(r) : "r"(a) : "memory");
  return r;
}
__device__ __forceinline__ void lds64(uint32_t* r, uint32_t a) {
  asm volatile("ld.shared.v2.b32 {%0,%1}, [%2];" : "=r"(r[0]), "=r"(r[1]) : "r"(a) : "memory");
}
__device__ __forceinline__ void sts32(uint32_t a, uint32_t v) {
  asm volatile("st.shared.b32 [%0], %1;" ::"r"(a), "r"(v) : "memory");
}
__device__ __forceinline__ void sts16(uint32_t a, uint32_t v) {
  asm volatile("st.shared.u16 [%0], %1;" ::"r"(a), "r"(v) : "memory");
}
__device__ __forceinline__ void mma_bf16(float* c, uint32_t a0, uint32_t a1, uint32_t a2, uint32_t a3, const uint32_t* b) {
  asm volatile("mma.sync.aligned.m16n8k16.row.col.f32.bf16.bf16.f32 {%0,%1,%2,%3}, {%4,%5,%6,%7}, {%8,%9}, {%0,%1,%2,%3};"
               : "+f"(c[0]), "+f"(c[1]), "+f"(c[2]), "+f"(c[3])
               : "r"(a0), "r"(a1), "r"(a2), "r"(a3), "r"(b[0]), "r"(b[1]));
}
__device__ __forceinline__ void wg_bar(int wg) { asm volatile("bar.sync %0, 128;" ::"r"(wg + 1) : "memory"); }
__device__ __forceinline__ void stsm4(uint32_t a, const uint32_t* r) {
  asm volatile("stmatrix.sync.aligned.m8n8.x4.shared.b16 [%0], {%1,%2,%3,%4};"
               ::"r"(a), "r"(r[0]), "r"(r[1]), "r"(r[2]), "r"(r[3]) : "memory");
}
__device__ __forceinline__ void sts128(uint32_t a, const uint32_t* r) {
  asm volatile("st.shared.v4.b32 [%0], {%1,%2,%3,%4};" ::"r"(a), "r"(r[0]), "r"(r[1]), "r"(r[2]), "r"(r[3]) : "memory");
}
__device__ __forceinline__ void lds128(uint32_t* r, uint32_t a) {
  asm volatile("ld.shared.v4.b32 {%0,%1,%2,%3}, [%4];" : "=r"(r[0]), "=r"(r[1]), "=r"(r[2]), "=r"(r[3]) : "r"(a) : "memory");
}
__device__ __forceinline__ uint32_t pack_bf16(float lo, float hi) {
  uint32_t r;
  asm("cvt.rn.bf16x2.f32 %0, %1, %2;" : "=r"(r) : "f"(hi), "f"(lo));
  return r;
}
__device__ __forceinline__ float bf_lo(uint32_t v) { return __uint_as_float(v << 16); }
__device__ __forceinline__ float bf_hi(uint32_t v) { return __uint_as_float(v & 0xffff0000u); }
__device__ __forceinline__ float round_bf16(float v) { return __uint_as_float(pack_bf16(0.f, v)); }
__device__ __forceinline__ uint32_t sub_bf16x2(uint32_t a, uint32_t b) {
  uint32_t r;
  asm("sub.rn.bf16x2 %0, %1, %2;" : "=r"(r) : "r"(a), "r"(b));
  return r;
}
__device__ __forceinline__ uint32_t add_bf16x2(uint32_t a, uint32_t b) {
  uint32_t r;
  asm("add.rn.bf16x2 %0, %1, %2;" : "=r"(r) : "r"(a), "r"(b));
  return r;
}
__device__ __forceinline__ uint32_t mul_bf16x2(uint32_t a, uint32_t b) {
  uint32_t r;
  asm("mul.rn.bf16x2 %0, %1, %2;" : "=r"(r) : "r"(a), "r"(b));
  return r;
}
__device__ __forceinline__ uint32_t fma_bf16x2(uint32_t a, uint32_t b, uint32_t c) {
  uint32_t r;
  asm("fma.rn.bf16x2 %0, %1, %2, %3;" : "=r"(r) : "r"(a), "r"(b), "r"(c));
  return r;
}
__device__ __forceinline__ float ln_rstd(float var) {
  float sd, r;
  asm("sqrt.approx.ftz.f32 %0, %1;" : "=f"(sd) : "f"(round_bf16(round_bf16(var) + 1e-5f)));
  asm("rcp.approx.ftz.f32 %0, %1;" : "=f"(r) : "f"(round_bf16(sd)));
  return r;
}
__device__ __forceinline__ float tanh_hw(float x) {
  float r;
  asm("tanh.approx.f32 %0, %1;" : "=f"(r) : "f"(x));
  return r;
}
__device__ __forceinline__ unsigned ld_acquire(const unsigned* p) {
  unsigned v;
  asm volatile("ld.acquire.gpu.global.u32 %0, [%1];" : "=r"(v) : "l"(p) : "memory");
  return v;
}
__device__ __forceinline__ void wait_flag(const unsigned* p, unsigned target) {
  uint32_t c = 0;
  while ((int)(ld_acquire(p) - target) < 0) {
    if (++c > SPIN_LIMIT) __trap();
  }
}
__device__ __forceinline__ void red_add(unsigned* p, unsigned v) {
  asm volatile("red.relaxed.gpu.global.add.u32 [%0], %1;" ::"l"(p), "r"(v) : "memory");
}
#define WG_FENCE() asm volatile("wgmma.fence.sync.aligned;" ::: "memory")
#define WG_COMMIT() asm volatile("wgmma.commit_group.sync.aligned;" ::: "memory")
#define WG_WAIT(n) asm volatile("wgmma.wait_group.sync.aligned %0;" ::"n"(n) : "memory")

template <int TB>
__device__ __forceinline__ void wgmma_n16(float* d, const uint32_t* a, uint64_t db, int accum) {
  asm volatile(
      "{\n.reg .pred p;\nsetp.ne.b32 p, %13, 0;\n"
      "wgmma.mma_async.sync.aligned.m64n16k16.f32.bf16.bf16 "
      "{%0,%1,%2,%3,%4,%5,%6,%7}, "
      "{%8,%9,%10,%11}, %12, p, 1, 1, %14;\n}\n"
      : "+f"(d[0]), "+f"(d[1]), "+f"(d[2]), "+f"(d[3]), "+f"(d[4]), "+f"(d[5]), "+f"(d[6]), "+f"(d[7])
      : "r"(a[0]), "r"(a[1]), "r"(a[2]), "r"(a[3]), "l"(db), "r"(accum), "n"(TB));
}
template <int TB>
__device__ __forceinline__ void wgmma_n32(float* d, const uint32_t* a, uint64_t db, int accum) {
  asm volatile(
      "{\n.reg .pred p;\nsetp.ne.b32 p, %21, 0;\n"
      "wgmma.mma_async.sync.aligned.m64n32k16.f32.bf16.bf16 "
      "{%0,%1,%2,%3,%4,%5,%6,%7,%8,%9,%10,%11,%12,%13,%14,%15}, "
      "{%16,%17,%18,%19}, %20, p, 1, 1, %22;\n}\n"
      : "+f"(d[0]), "+f"(d[1]), "+f"(d[2]), "+f"(d[3]), "+f"(d[4]), "+f"(d[5]), "+f"(d[6]), "+f"(d[7]),
        "+f"(d[8]), "+f"(d[9]), "+f"(d[10]), "+f"(d[11]), "+f"(d[12]), "+f"(d[13]), "+f"(d[14]), "+f"(d[15])
      : "r"(a[0]), "r"(a[1]), "r"(a[2]), "r"(a[3]), "l"(db), "r"(accum), "n"(TB));
}
template <int TB>
__device__ __forceinline__ void wgmma_n48(float* d, const uint32_t* a, uint64_t db, int accum) {
  asm volatile(
      "{\n.reg .pred p;\nsetp.ne.b32 p, %29, 0;\n"
      "wgmma.mma_async.sync.aligned.m64n48k16.f32.bf16.bf16 "
      "{%0,%1,%2,%3,%4,%5,%6,%7,%8,%9,%10,%11,%12,%13,%14,%15,%16,%17,%18,%19,%20,%21,%22,%23}, "
      "{%24,%25,%26,%27}, %28, p, 1, 1, %30;\n}\n"
      : "+f"(d[0]), "+f"(d[1]), "+f"(d[2]), "+f"(d[3]), "+f"(d[4]), "+f"(d[5]), "+f"(d[6]), "+f"(d[7]),
        "+f"(d[8]), "+f"(d[9]), "+f"(d[10]), "+f"(d[11]), "+f"(d[12]), "+f"(d[13]), "+f"(d[14]), "+f"(d[15]),
        "+f"(d[16]), "+f"(d[17]), "+f"(d[18]), "+f"(d[19]), "+f"(d[20]), "+f"(d[21]), "+f"(d[22]), "+f"(d[23])
      : "r"(a[0]), "r"(a[1]), "r"(a[2]), "r"(a[3]), "l"(db), "r"(accum), "n"(TB));
}
template <int TB>
__device__ __forceinline__ void wgmma_n64(float* d, const uint32_t* a, uint64_t db, int accum) {
  asm volatile(
      "{\n.reg .pred p;\nsetp.ne.b32 p, %37, 0;\n"
      "wgmma.mma_async.sync.aligned.m64n64k16.f32.bf16.bf16 "
      "{%0,%1,%2,%3,%4,%5,%6,%7,%8,%9,%10,%11,%12,%13,%14,%15,%16,%17,%18,%19,%20,%21,%22,%23,%24,%25,%26,%27,%28,%29,%30,%31}, "
      "{%32,%33,%34,%35}, %36, p, 1, 1, %38;\n}\n"
      : "+f"(d[0]), "+f"(d[1]), "+f"(d[2]), "+f"(d[3]), "+f"(d[4]), "+f"(d[5]), "+f"(d[6]), "+f"(d[7]),
        "+f"(d[8]), "+f"(d[9]), "+f"(d[10]), "+f"(d[11]), "+f"(d[12]), "+f"(d[13]), "+f"(d[14]), "+f"(d[15]),
        "+f"(d[16]), "+f"(d[17]), "+f"(d[18]), "+f"(d[19]), "+f"(d[20]), "+f"(d[21]), "+f"(d[22]), "+f"(d[23]),
        "+f"(d[24]), "+f"(d[25]), "+f"(d[26]), "+f"(d[27]), "+f"(d[28]), "+f"(d[29]), "+f"(d[30]), "+f"(d[31])
      : "r"(a[0]), "r"(a[1]), "r"(a[2]), "r"(a[3]), "l"(db), "r"(accum), "n"(TB));
}
template <int TB>
__device__ __forceinline__ void wgmma_n80(float* d, const uint32_t* a, uint64_t db, int accum) {
  asm volatile(
      "{\n.reg .pred p;\nsetp.ne.b32 p, %45, 0;\n"
      "wgmma.mma_async.sync.aligned.m64n80k16.f32.bf16.bf16 "
      "{%0,%1,%2,%3,%4,%5,%6,%7,%8,%9,%10,%11,%12,%13,%14,%15,%16,%17,%18,%19,%20,%21,%22,%23,%24,%25,%26,%27,%28,%29,%30,%31,%32,%33,%34,%35,%36,%37,%38,%39}, "
      "{%40,%41,%42,%43}, %44, p, 1, 1, %46;\n}\n"
      : "+f"(d[0]), "+f"(d[1]), "+f"(d[2]), "+f"(d[3]), "+f"(d[4]), "+f"(d[5]), "+f"(d[6]), "+f"(d[7]),
        "+f"(d[8]), "+f"(d[9]), "+f"(d[10]), "+f"(d[11]), "+f"(d[12]), "+f"(d[13]), "+f"(d[14]), "+f"(d[15]),
        "+f"(d[16]), "+f"(d[17]), "+f"(d[18]), "+f"(d[19]), "+f"(d[20]), "+f"(d[21]), "+f"(d[22]), "+f"(d[23]),
        "+f"(d[24]), "+f"(d[25]), "+f"(d[26]), "+f"(d[27]), "+f"(d[28]), "+f"(d[29]), "+f"(d[30]), "+f"(d[31]),
        "+f"(d[32]), "+f"(d[33]), "+f"(d[34]), "+f"(d[35]), "+f"(d[36]), "+f"(d[37]), "+f"(d[38]), "+f"(d[39])
      : "r"(a[0]), "r"(a[1]), "r"(a[2]), "r"(a[3]), "l"(db), "r"(accum), "n"(TB));
}
template <int TB>
__device__ __forceinline__ void wgmma_n96(float* d, const uint32_t* a, uint64_t db, int accum) {
  asm volatile(
      "{\n.reg .pred p;\nsetp.ne.b32 p, %53, 0;\n"
      "wgmma.mma_async.sync.aligned.m64n96k16.f32.bf16.bf16 "
      "{%0,%1,%2,%3,%4,%5,%6,%7,%8,%9,%10,%11,%12,%13,%14,%15,%16,%17,%18,%19,%20,%21,%22,%23,%24,%25,%26,%27,%28,%29,%30,%31,%32,%33,%34,%35,%36,%37,%38,%39,%40,%41,%42,%43,%44,%45,%46,%47}, "
      "{%48,%49,%50,%51}, %52, p, 1, 1, %54;\n}\n"
      : "+f"(d[0]), "+f"(d[1]), "+f"(d[2]), "+f"(d[3]), "+f"(d[4]), "+f"(d[5]), "+f"(d[6]), "+f"(d[7]),
        "+f"(d[8]), "+f"(d[9]), "+f"(d[10]), "+f"(d[11]), "+f"(d[12]), "+f"(d[13]), "+f"(d[14]), "+f"(d[15]),
        "+f"(d[16]), "+f"(d[17]), "+f"(d[18]), "+f"(d[19]), "+f"(d[20]), "+f"(d[21]), "+f"(d[22]), "+f"(d[23]),
        "+f"(d[24]), "+f"(d[25]), "+f"(d[26]), "+f"(d[27]), "+f"(d[28]), "+f"(d[29]), "+f"(d[30]), "+f"(d[31]),
        "+f"(d[32]), "+f"(d[33]), "+f"(d[34]), "+f"(d[35]), "+f"(d[36]), "+f"(d[37]), "+f"(d[38]), "+f"(d[39]),
        "+f"(d[40]), "+f"(d[41]), "+f"(d[42]), "+f"(d[43]), "+f"(d[44]), "+f"(d[45]), "+f"(d[46]), "+f"(d[47])
      : "r"(a[0]), "r"(a[1]), "r"(a[2]), "r"(a[3]), "l"(db), "r"(accum), "n"(TB));
}
template <int TB>
__device__ __forceinline__ void wgmma_n112(float* d, const uint32_t* a, uint64_t db, int accum) {
  asm volatile(
      "{\n.reg .pred p;\nsetp.ne.b32 p, %61, 0;\n"
      "wgmma.mma_async.sync.aligned.m64n112k16.f32.bf16.bf16 "
      "{%0,%1,%2,%3,%4,%5,%6,%7,%8,%9,%10,%11,%12,%13,%14,%15,%16,%17,%18,%19,%20,%21,%22,%23,%24,%25,%26,%27,%28,%29,%30,%31,%32,%33,%34,%35,%36,%37,%38,%39,%40,%41,%42,%43,%44,%45,%46,%47,%48,%49,%50,%51,%52,%53,%54,%55}, "
      "{%56,%57,%58,%59}, %60, p, 1, 1, %62;\n}\n"
      : "+f"(d[0]), "+f"(d[1]), "+f"(d[2]), "+f"(d[3]), "+f"(d[4]), "+f"(d[5]), "+f"(d[6]), "+f"(d[7]),
        "+f"(d[8]), "+f"(d[9]), "+f"(d[10]), "+f"(d[11]), "+f"(d[12]), "+f"(d[13]), "+f"(d[14]), "+f"(d[15]),
        "+f"(d[16]), "+f"(d[17]), "+f"(d[18]), "+f"(d[19]), "+f"(d[20]), "+f"(d[21]), "+f"(d[22]), "+f"(d[23]),
        "+f"(d[24]), "+f"(d[25]), "+f"(d[26]), "+f"(d[27]), "+f"(d[28]), "+f"(d[29]), "+f"(d[30]), "+f"(d[31]),
        "+f"(d[32]), "+f"(d[33]), "+f"(d[34]), "+f"(d[35]), "+f"(d[36]), "+f"(d[37]), "+f"(d[38]), "+f"(d[39]),
        "+f"(d[40]), "+f"(d[41]), "+f"(d[42]), "+f"(d[43]), "+f"(d[44]), "+f"(d[45]), "+f"(d[46]), "+f"(d[47]),
        "+f"(d[48]), "+f"(d[49]), "+f"(d[50]), "+f"(d[51]), "+f"(d[52]), "+f"(d[53]), "+f"(d[54]), "+f"(d[55])
      : "r"(a[0]), "r"(a[1]), "r"(a[2]), "r"(a[3]), "l"(db), "r"(accum), "n"(TB));
}
template <int TB>
__device__ __forceinline__ void wgmma_n128(float* d, const uint32_t* a, uint64_t db, int accum) {
  asm volatile(
      "{\n.reg .pred p;\nsetp.ne.b32 p, %69, 0;\n"
      "wgmma.mma_async.sync.aligned.m64n128k16.f32.bf16.bf16 "
      "{%0,%1,%2,%3,%4,%5,%6,%7,%8,%9,%10,%11,%12,%13,%14,%15,%16,%17,%18,%19,%20,%21,%22,%23,%24,%25,%26,%27,%28,%29,%30,%31,%32,%33,%34,%35,%36,%37,%38,%39,%40,%41,%42,%43,%44,%45,%46,%47,%48,%49,%50,%51,%52,%53,%54,%55,%56,%57,%58,%59,%60,%61,%62,%63}, "
      "{%64,%65,%66,%67}, %68, p, 1, 1, %70;\n}\n"
      : "+f"(d[0]), "+f"(d[1]), "+f"(d[2]), "+f"(d[3]), "+f"(d[4]), "+f"(d[5]), "+f"(d[6]), "+f"(d[7]),
        "+f"(d[8]), "+f"(d[9]), "+f"(d[10]), "+f"(d[11]), "+f"(d[12]), "+f"(d[13]), "+f"(d[14]), "+f"(d[15]),
        "+f"(d[16]), "+f"(d[17]), "+f"(d[18]), "+f"(d[19]), "+f"(d[20]), "+f"(d[21]), "+f"(d[22]), "+f"(d[23]),
        "+f"(d[24]), "+f"(d[25]), "+f"(d[26]), "+f"(d[27]), "+f"(d[28]), "+f"(d[29]), "+f"(d[30]), "+f"(d[31]),
        "+f"(d[32]), "+f"(d[33]), "+f"(d[34]), "+f"(d[35]), "+f"(d[36]), "+f"(d[37]), "+f"(d[38]), "+f"(d[39]),
        "+f"(d[40]), "+f"(d[41]), "+f"(d[42]), "+f"(d[43]), "+f"(d[44]), "+f"(d[45]), "+f"(d[46]), "+f"(d[47]),
        "+f"(d[48]), "+f"(d[49]), "+f"(d[50]), "+f"(d[51]), "+f"(d[52]), "+f"(d[53]), "+f"(d[54]), "+f"(d[55]),
        "+f"(d[56]), "+f"(d[57]), "+f"(d[58]), "+f"(d[59]), "+f"(d[60]), "+f"(d[61]), "+f"(d[62]), "+f"(d[63])
      : "r"(a[0]), "r"(a[1]), "r"(a[2]), "r"(a[3]), "l"(db), "r"(accum), "n"(TB));
}
template <int N, int TB>
__device__ __forceinline__ void wgmma_rs(float* d, const uint32_t* a, uint64_t db, int accum) {
  if constexpr (N == 16) wgmma_n16<TB>(d, a, db, accum);
  if constexpr (N == 32) wgmma_n32<TB>(d, a, db, accum);
  if constexpr (N == 48) wgmma_n48<TB>(d, a, db, accum);
  if constexpr (N == 64) wgmma_n64<TB>(d, a, db, accum);
  if constexpr (N == 80) wgmma_n80<TB>(d, a, db, accum);
  if constexpr (N == 96) wgmma_n96<TB>(d, a, db, accum);
  if constexpr (N == 112) wgmma_n112<TB>(d, a, db, accum);
  if constexpr (N == 128) wgmma_n128<TB>(d, a, db, accum);
}

struct SsmParams {
  const __nv_bfloat16 *x, *a_re, *a_im, *b_re, *b_im, *c_re, *c_im, *log_dt, *dskip, *w1, *w3, *w2;
  Scratch* g;
};
struct C2 {
  float r, i;
};
__device__ __forceinline__ C2 cmul(C2 a, C2 b) { return {fmaf(a.r, b.r, -a.i * b.i), fmaf(a.r, b.i, a.i * b.r)}; }
__device__ __forceinline__ C2 cmulc(C2 a, C2 b) { return {fmaf(a.r, b.r, a.i * b.i), fmaf(a.i, b.r, -a.r * b.i)}; }
__device__ __forceinline__ C2 cexp_pow(float a2, float rev, float l) {
  float m, t = rev * l, sn, cs;
  asm("ex2.approx.ftz.f32 %0, %1;" : "=f"(m) : "f"(a2 * l));
  t = (t - rintf(t)) * 6.283185307179586f;
  asm("sin.approx.ftz.f32 %0, %1;" : "=f"(sn) : "f"(t));
  asm("cos.approx.ftz.f32 %0, %1;" : "=f"(cs) : "f"(t));
  return {m * cs, m * sn};
}
__device__ __forceinline__ void store8(uint32_t addr, const C2* v) {
  uint32_t re[4], im[4];
#pragma unroll
  for (int i = 0; i < 4; i++) {
    re[i] = pack_bf16(v[2 * i].r, v[2 * i + 1].r);
    im[i] = pack_bf16(v[2 * i].i, v[2 * i + 1].i);
  }
  sts128(addr, re);
  sts128(addr + WS_WARP / 2, im);
}
struct ModeIn {
  uint32_t ar, ai, br, bi, cr, ci, ldt;
};
__device__ __forceinline__ uint32_t ldg16(const __nv_bfloat16* p) {
  uint32_t r;
  asm volatile("ld.global.nc.u16 %0, [%1];" : "=r"(r) : "l"(p));
  return r;
}
__device__ __forceinline__ uint32_t ldg32(const __nv_bfloat16* p) {
  uint32_t r;
  asm volatile("ld.global.nc.u32 %0, [%1];" : "=r"(r) : "l"(p));
  return r;
}
__device__ __forceinline__ ModeIn load_modes(const SsmParams& p, uint32_t d, uint32_t pair) {
  const uint32_t i = d * NMODE + 2 * pair;
  return {ldg32(p.a_re + i), ldg32(p.a_im + i), ldg32(p.b_re + i), ldg32(p.b_im + i),
          ldg32(p.c_re + i), ldg32(p.c_im + i), ldg16(p.log_dt + d)};
}

__device__ __forceinline__ void kgen_modes(uint32_t my, const ModeIn in, uint32_t sel, float (&acc)[6][4]) {
  const int lane = fresh_tid() & 31;
  const uint32_t row = my + lane * 112;
  auto pick = [&](uint32_t v) { return __uint_as_float(__byte_perm(v, 0, sel)); };
  const float dt = round_bf16(__expf(bf_lo(in.ldt)));
  const float a2 = dt * pick(in.ar) * 1.4426950408889634f, rev = dt * pick(in.ai) * 0.15915494309189535f;
  const C2 e1 = cexp_pow(a2, rev, 1.f), e8 = cexp_pow(a2, rev, 8.f), e256 = cexp_pow(a2, rev, 256.f);
  {
    C2 y[8];
    y[0] = {1.f, 0.f};
    y[1] = e8;
    y[2] = cmul(e8, e8);
    y[3] = cmul(y[2], e8);
    y[4] = cmul(y[2], y[2]);
    y[5] = cmul(y[4], y[1]);
    y[6] = cmul(y[4], y[2]);
    y[7] = cmul(y[4], y[3]);
    const C2 e64 = cmul(y[4], y[4]);
    store8(row, y);
#pragma unroll
    for (int c = 1; c < 4; c++) {
#pragma unroll
      for (int i = 0; i < 8; i++) y[i] = (c == 1 && i == 0) ? e64 : cmul(y[i], e64);
      store8(row + 16 * c, y);
    }
  }
  {
    C2 x[8], z[8];
    x[0] = cmulc({pick(in.cr), -pick(in.ci)}, {dt * pick(in.br), dt * pick(in.bi)});
    x[1] = cmulc(x[0], e1);
    const C2 e2 = cmul(e1, e1);
#pragma unroll
    for (int i = 2; i < 8; i++) x[i] = cmulc(x[i - 2], e2);
    store8(row + 64, x);
#pragma unroll
    for (int i = 0; i < 4; i++) z[i] = cmulc(x[2 * i], e256);
    z[4] = cmulc(z[0], e256);
    z[5] = cmulc(z[2], e256);
    z[6] = cmulc(z[4], e256);
    z[7] = cmulc(z[5], e256);
    store8(row + 80, z);
    const C2 e512 = cmul(e256, e256);
    x[0] = cmulc(z[4], e512);
    x[1] = cmulc(z[6], e512);
    x[2] = cmulc(x[0], e512);
    x[3] = cmulc(x[1], e512);
    x[4] = cmulc(x[2], e512);
    x[5] = x[6] = x[7] = {0.f, 0.f};
    store8(row + 96, x);
  }
  __syncwarp();
  const uint32_t aa = my + (lane >> 4) * (WS_WARP / 2) + (lane & 7) * 112 + ((lane >> 3) & 1) * 16;
  const uint32_t ba = my + ((lane >> 3) & 1) * (WS_WARP / 2) + (lane & 7) * 112 + (lane >> 4) * 16 + 64;
#pragma unroll
  for (int ks = 0; ks < 4; ks++) {
    uint32_t a[2][4], b[6];
    ldsm4t(a[0], aa + ks * 896);
    ldsm4t(a[1], aa + ks * 896 + 32);
    ldsm4t(b, ba + ks * 896);
    ldsm2t(b + 4, ba + ks * 896 + 32);
#pragma unroll
    for (int nt = 0; nt < 3; nt++)
#pragma unroll
      for (int mt = 0; mt < 2; mt++) mma_bf16(acc[nt * 2 + mt], a[mt][0], a[mt][1], a[mt][2], a[mt][3], &b[2 * nt]);
  }
  __syncwarp();
}

__device__ __forceinline__ void stats_load(Scratch* g, uint32_t (&st)[12]) {
  const uint4* sp = &g->stats[fresh_tid()];
#pragma unroll
  for (int e = 0; e < 3; e++) {
    uint32_t* v = &st[4 * e];
    asm volatile("ld.relaxed.gpu.global.v4.b32 {%0,%1,%2,%3}, [%4];"
                 : "=r"(v[0]), "=r"(v[1]), "=r"(v[2]), "=r"(v[3]) : "l"(sp + 256 * e) : "memory");
  }
}
__device__ __forceinline__ void kgen_finish(uint32_t sb, Scratch* g, int wg, const float (&acc)[6][4], uint32_t (&st)[12]) {
  const int t = fresh_tid() & 127;
  const uint32_t ws = sb + OFF_WS + wg * WS_BYTES;
#pragma unroll
  for (int i = 0; i < 6; i++)
    sts128(ws + (t >> 5) * WS_WARP + i * 512 + (t & 31) * 16, reinterpret_cast<const uint32_t*>(acc[i]));
  if (t < 2) sts32(ws + WS_KC - 4 + t * KC_PITCH, 0);
  STAMPC(threadIdx.x == 0, 15);
  wg_bar(wg);
  STAMPC(threadIdx.x == 0, 16);
  {
    uint32_t v[3][4][2], pk[3][2];
#pragma unroll
    for (int k = 0; k < 3; k++)
#pragma unroll
      for (int src = 0; src < 4; src++) lds64(v[k][src], ws + src * WS_WARP + k * 1024 + t * 8);
    const float f = wg == 2 ? 1.f : 0.f;
#pragma unroll
    for (int k = 0; k < 3; k++) {
      const float b0 = __uint_as_float(v[k][2][0]) + __uint_as_float(v[k][3][0]);
      const float b1 = __uint_as_float(v[k][2][1]) + __uint_as_float(v[k][3][1]);
      const float a0 = __uint_as_float(v[k][0][0]) + __uint_as_float(v[k][1][0]);
      const float a1 = __uint_as_float(v[k][0][1]) + __uint_as_float(v[k][1][1]);
      pk[k][0] = f != 0.f ? pack_bf16(a0 + b0, a1 + b1) : pack_bf16(a0, a1);
      pk[k][1] = pack_bf16(b0, b1);
    }
    const int q = (t >> 1) & 3, j = (t >> 6) * 16 + ((t >> 3) & 7) + (t & 1) * 8;
#pragma unroll
    for (int ch = 0; ch < 2; ch++) {
      const uint32_t kc = ws + WS_KC + ch * KC_PITCH;
      sts32(kc + 2 * (8 * j + 2 * q), pk[0][ch]);
      sts32(kc + 2 * (q < 2 ? 256 + 4 * j + 2 * q : 256 + 64 * q + 2 * j), pk[1][ch]);
      if (q < 2 || (q == 2 && j == 0)) sts16(kc + 2 * (512 + 64 * q + j), pk[2][ch]);
      if (q < 2) sts16(kc + 2 * (544 + 64 * q + j), pk[2][ch] >> 16);
    }
  }
  wg_bar(wg);
  STAMPC(threadIdx.x == 0, 17);
  if (wg < 2) stats_load(g, st);
  uint32_t v[2][9];
  const bool dense = t < 64;
#pragma unroll
  for (int ch = 0; ch < 2; ch++) {
    const uint32_t kc = ws + WS_KC + ch * KC_PITCH, k0 = kc + (dense ? 8 * t : 256 + 4 * t);
    v[ch][0] = lds32(k0);
    v[ch][1] = lds32(k0 + 4);
    v[ch][2] = lds16(k0 - (t <= 64 ? 2 : 0));
    v[ch][3] = lds16(kc + 2 * (384 + t));
    v[ch][4] = lds16(kc + 2 * (385 + t));
#pragma unroll
    for (int k = 0; k < 2; k++) {
      v[ch][5 + 2 * k] = lds16(kc + 2 * (512 + 64 * k + (t >> 1)));
      v[ch][6 + 2 * k] = lds16(kc + 2 * (512 + 64 * k + ((t + 1) >> 1)));
    }
  }
  const uint32_t s1 = dense ? 0x1032 : 0x1010, s2 = dense ? 0x7610 : 0x5476, s3 = dense ? 0x1032 : 0x7610;
#pragma unroll
  for (int ch = 0; ch < 2; ch++) {
    if (ch == 1 && wg == 2) break;
    const uint32_t pkb = sb + OFF_PK + (2 * wg + ch) * PK_PITCH + 32 + t * 16;
    uint32_t o[4];
    o[0] = __byte_perm(v[ch][0], v[ch][2], 0x5410);
    o[1] = __byte_perm(v[ch][0], 0, s1);
    o[2] = __byte_perm(v[ch][1], v[ch][0], s2);
    o[3] = __byte_perm(v[ch][1], v[ch][0], s3);
    sts128(pkb, o);
    uint32_t vm = (t & 1) ? v[ch][4] : v[ch][3];
    o[0] = o[1] = __byte_perm(v[ch][3], 0, 0x1010);
    o[2] = __byte_perm(vm, v[ch][3], 0x5410);
    o[3] = __byte_perm(v[ch][4], vm, 0x5410);
    sts128(pkb + 2048, o);
#pragma unroll
    for (int k = 0; k < 2; k++) {
      const uint32_t v0 = v[ch][5 + 2 * k], v1 = v[ch][6 + 2 * k];
      vm = (t & 2) ? v1 : v0;
      o[0] = __byte_perm(vm, v0, 0x5410);
      o[1] = __byte_perm(v1, vm, 0x5410);
      o[2] = o[3] = __byte_perm(v1, 0, 0x1010);
      sts128(pkb + 4096 + 2048 * k, o);
    }
  }
}

__device__ __forceinline__ uint32_t copy_reg(uint32_t v) {
  uint32_t r;
  asm volatile("mov.b32 %0, %1;" : "=r"(r) : "r"(v));
  return r;
}
struct ConvCtx {
  uint32_t pa, pw, pr, ub, xb, dsk;
  uint64_t db;
  uint4* hrow;
  int wg, t;
  uint32_t sig;
};
__device__ __forceinline__ void conv_emit(const ConvCtx& c, int k) {
  uint32_t v[6][4], h[4];
  wg_bar(c.wg);
#pragma unroll
  for (int src = 0; src < 4; src++) lds128(v[src], k == 0 && c.t < src ? c.ub - 64 : c.pr + src * 4080 + 2048 * k);
  lds128(v[4], c.ub + 2048 * k);
  lds128(v[5], c.xb + 2048 * k);
#pragma unroll
  for (int e = 0; e < 4; e++) {
    const uint32_t y = add_bf16x2(add_bf16x2(v[0][e], v[1][e]), add_bf16x2(v[2][e], v[3][e]));
    h[e] = add_bf16x2(v[5][e], add_bf16x2(y, mul_bf16x2(v[4][e], c.dsk)));
  }
  c.hrow[128 * k] = make_uint4(h[0], h[1], h[2], h[3]);
}
__device__ __forceinline__ void conv_spill(const ConvCtx& c, const float* acc, int b) {
  uint32_t p[4];
#pragma unroll
  for (int e = 0; e < 4; e++) p[e] = pack_bf16(acc[2 * e], acc[2 * e + 1]);
  asm volatile("stmatrix.sync.aligned.m8n8.x4.trans.shared.b16 [%0], {%1,%2,%3,%4};"
               ::"r"(c.pw + b * 512), "r"(p[0]), "r"(p[1]), "r"(p[2]), "r"(p[3]) : "memory");
}
template <int B>
__device__ __forceinline__ void conv_batches(const ConvCtx& c, float (&acc)[64], uint32_t (&a)[2][4][4]) {
  constexpr int N = (B + 1) & 1;
  WG_FENCE();
#pragma unroll
  for (int k = 0; k < 4; k++) wgmma_rs<128 - 16 * B, 0>(acc + 8 * B, a[B & 1][k], c.db - 16 * (k >> 1) - 4 * (k & 1), B + k);
  WG_COMMIT();
  if constexpr (B < 7) {
#pragma unroll
    for (int k = 0; k < 4; k++) {
      const uint32_t o = c.pa + 1024 * (B + 1) + 512 * (k >> 1) + 128 * (k & 1);
      a[N][k][0] = lds32(o);
      a[N][k][1] = lds32(o + 256);
    }
  }
  if constexpr (B == 0) wg_bar(c.wg);
  if constexpr (B > 0) conv_spill(c, acc + 8 * (B - 1), B - 1);
  if constexpr (B == 4) {
    conv_emit(c, 0);
    __syncwarp();
    if (c.sig) mbar_arrive(c.sig);
  }
  WG_WAIT(0);
#pragma unroll
  for (int i = 8 * B; i < 64; i++) asm volatile("mov.b32 %0, %1;" : "=f"(acc[i]) : "f"(acc[i]));
  if constexpr (B < 7) {
#pragma unroll
    for (int k = 0; k < 4; k++) {
      a[N][k][2] = copy_reg(k < 2 ? a[B & 1][k + 2][1] : a[N][k - 2][1]);
      a[N][k][3] = copy_reg(a[N][k][0]);
    }
    conv_batches<B + 1>(c, acc, a);
  }
}

__device__ __forceinline__ void conv_task(uint32_t sb, Scratch* g, int wg, int w, int local, int d, bool last) {
  const int t = fresh_tid() & 127, lane = t & 31;
  const uint32_t ub = sb + OFF_U + local * U_PITCH + U_PAD, part = sb + OFF_PART + wg * SLOT;
  ConvCtx c;
  c.pa = sb + OFF_PK + local * PK_PITCH + 32 + 4 * (8 * w + (lane >> 2) - 2 * (lane & 3));
  c.pw = part + w * 4096 + lane * 16;
  c.pr = part + 16 * t;
  c.ub = ub + 16 * t;
  c.xb = sb + OFF_X + local * X_PITCH + 16 * t;
  c.dsk = lds32(sb + OFF_MISC + 120 + 4 * local);
  c.db = (uint64_t)((ub & 0x3FFFF) >> 4) | ((uint64_t)(128 >> 4) << 16) | ((uint64_t)(256 >> 4) << 32);
  c.hrow = reinterpret_cast<uint4*>(g->hT + d * L) + t;
  c.wg = wg;
  c.t = t;
  c.sig = last && lane == 0 ? sb + B_CV : 0;
  float acc[64];
  uint32_t a[2][4][4];
#pragma unroll
  for (int k = 0; k < 4; k++) {
    const uint32_t o = c.pa + 512 * (k >> 1) + 128 * (k & 1);
    a[0][k][0] = lds32(o);
    a[0][k][1] = lds32(o + 256);
    a[0][k][2] = copy_reg(k < 2 ? 0 : a[0][k & 1][1]);
    a[0][k][3] = copy_reg(a[0][k][0]);
  }
  conv_batches<0>(c, acc, a);
  STAMP(32 + wg + 3 * last);
  conv_spill(c, acc + 56, 7);
  conv_emit(c, 1);
}

__device__ __forceinline__ void mma_k8(float* c, uint32_t a0, uint32_t a1, uint32_t b) {
  asm volatile("mma.sync.aligned.m16n8k8.row.col.f32.bf16.bf16.f32 {%0,%1,%2,%3}, {%4,%5}, {%6}, {%0,%1,%2,%3};"
               : "+f"(c[0]), "+f"(c[1]), "+f"(c[2]), "+f"(c[3]) : "r"(a0), "r"(a1), "r"(b));
}

__device__ __forceinline__ void ln1_stats(uint32_t sb, Scratch* g, int c, const uint4 (&xv)[9]) {
  const int t = fresh_tid() & 127, lane = t & 31;
  float st[5][4];
#pragma unroll
  for (int i = 0; i < 5; i++) st[i][0] = st[i][1] = st[i][2] = st[i][3] = 0.f;
  const uint32_t ones[2] = {0x3f803f80u, 0x3f803f80u};
  STAMPC(t == 0 && xv[0].x != 0x12345, 44);
#pragma unroll
  for (int i = 0; i < 9; i++) {
    mma_bf16(st[0], xv[i].x, xv[i].y, xv[i].z, xv[i].w, ones);
    mma_k8(st[1], xv[i].x, xv[i].y, xv[i].x);
    mma_k8(st[2], xv[i].x, xv[i].y, xv[i].y);
    mma_k8(st[3], xv[i].z, xv[i].w, xv[i].z);
    mma_k8(st[4], xv[i].z, xv[i].w, xv[i].w);
  }
  float s = st[0][0] + st[0][2];
  float q = (lane & 4) ? (st[1][1] + st[3][1]) + (st[2][3] + st[4][3]) : (st[1][0] + st[3][0]) + (st[2][2] + st[4][2]);
  STAMPC(t == 0 && q != 1234.f, 45);
  s += __shfl_xor_sync(~0u, s, 4);
  q += __shfl_xor_sync(~0u, q, 4);
  q = __shfl_sync(~0u, q, (lane & 24) + (lane >> 3));
  const float m = s * (1.f / D), r = ln_rstd(fmaxf(q * (1.f / D) - m * m, 0.f));
  const int sub = t & 7;
  const uint32_t b = pack_bf16(sub == 0 ? m : sub == 1 ? r : r - round_bf16(r), 0.f);
  if (sub < 3) sts16(sb + OFF_MISC + sub * 32 + (t >> 3) * 2, b ? b : 0x8000u);
  wg_bar(2);
  if (t < 6) {
    uint32_t v[4];
    lds128(v, sb + OFF_MISC + t * 16);
    asm volatile("st.relaxed.gpu.global.v4.b32 [%0], {%1,%2,%3,%4};" ::"l"(&g->stats[(t >> 1) * 256 + 2 * c + (t & 1)]),
                 "r"(v[0]), "r"(v[1]), "r"(v[2]), "r"(v[3]) : "memory");
  }
}

__device__ __forceinline__ void x_transpose(uint32_t sb, int c, int w) {
  const int lane = fresh_tid() & 31, rank = c & 1;
  uint32_t dx[2];
#pragma unroll
  for (int hf = 0; hf < 2; hf++) {
    const int rel = 8 * hf + (lane >> 2) - ((c >> 1) & 7), loc = rel > 4 ? rel - 5 : rel;
    dx[hf] = (rel > 4) == rank ? OFF_X + loc * X_PITCH + 2048 * rank : OFF_STG + loc * STG_PITCH;
    dx[hf] = rel >= 0 && rel < 9 ? sb + dx[hf] + 16 * (lane & 3) + 64 * w : 0;
  }
#pragma unroll 1
  for (int half = 0; half < 2; half++) {
    mbar_wait(sb + B_G + 8 * half, 0);
    STAMPC(w == 0 && lane == 0, 56 + half);
    uint32_t x[8][4];
#pragma unroll
    for (int i = 0; i < 8; i++)
      ldsm4t(x[i], sb + OFF_G + (16 * half + 4 * (i >> 1) + w) * 1024 + lane * 32 + (((i ^ (lane >> 2)) & 1) << 4));
#pragma unroll
    for (int i = 0; i < 8; i++)
      if (dx[i & 1]) sts128(dx[i & 1] + 1024 * half + 256 * (i >> 1), x[i]);
  }
  asm volatile("fence.proxy.async.shared::cta;" ::: "memory");
  wg_bar(2);
  if (elect_one()) {
    const uint32_t pb = mapa(sb, rank ^ 1), dst = pb + OFF_X + 2048 * rank;
    bulk_peer(dst + w * X_PITCH, sb + OFF_STG + w * STG_PITCH, 2048, pb + B_UX);
    if (w == 0) bulk_peer(dst + 4 * X_PITCH, sb + OFF_STG + 4 * STG_PITCH, 2048, pb + B_UX);
    if (w == 1) mbar_arrive(sb + B_UX);
  }
  __syncwarp();
}

__device__ __forceinline__ void ln1_apply(uint32_t sb, Scratch* g, uint32_t (&st)[12]) {
  const int t = fresh_tid();
  for (uint32_t spins = 0;; spins++) {
    uint32_t mn = ~0u;
#pragma unroll
    for (int e = 0; e < 12; e++) mn = min(mn, st[e]);
    if (__all_sync(~0u, mn != 0)) break;
    if (spins > SPIN_LIMIT) __trap();
    stats_load(g, st);
  }
  STAMPC(t == 0, 60);
  mbar_wait(sb + B_UX, 0);
  STAMPC(t == 0, 61);
  uint32_t x[5][4];
#pragma unroll
  for (int ch = 0; ch < 5; ch++) lds128(x[ch], sb + OFF_X + ch * X_PITCH + 16 * t);
#pragma unroll
  for (int ch = 0; ch < 5; ch++) {
#pragma unroll
    for (int e = 0; e < 4; e++) {
      const uint32_t dv = sub_bf16x2(x[ch][e], st[e]);
      x[ch][e] = fma_bf16x2(dv, st[4 + e], mul_bf16x2(dv, st[8 + e]));
    }
    sts128(sb + OFF_U + ch * U_PITCH + U_PAD + 16 * t, x[ch]);
  }
}

struct Ring {
  uint32_t slot, phase;
  __device__ __forceinline__ uint32_t off() const { return slot * SLOT; }
  __device__ __forceinline__ void next() {
    if (++slot == NS) { slot = 0; phase ^= 1; }
  }
};

__device__ __forceinline__ uint64_t bdesc(uint32_t addr) {
  return (uint64_t)((addr & 0x3FFFF) >> 4) | ((uint64_t)(BOX >> 4) << 16) | ((uint64_t)(1024 >> 4) << 32) | (1ull << 62);
}
__device__ __forceinline__ void release_slot(uint32_t sb, uint32_t slot, int lane) {
  if (lane == 0) mbar_arrive(sb + B_EMPTY + 8 * slot);
}
__device__ __forceinline__ void stage_partial(const float* acc, uint32_t addr) {
#pragma unroll
  for (int j = 0; j < 4; j++) {
    uint32_t p[4];
#pragma unroll
    for (int i = 0; i < 4; i++) p[i] = pack_bf16(acc[8 * j + 2 * i], acc[8 * j + 2 * i + 1]);
    sts128(addr + j * 512, p);
  }
}
__device__ __forceinline__ void stage_done(uint32_t bar, int lane) {
  asm volatile("fence.proxy.async.shared::cta;" ::: "memory");
  __syncwarp();
  if (lane == 0) mbar_arrive(bar);
}
__device__ __forceinline__ void lds128_if(uint32_t* r, uint32_t a, bool on) {
  asm volatile("{\n.reg .pred p;\nsetp.ne.u32 p, %5, 0;\n@p ld.shared.v4.b32 {%0,%1,%2,%3}, [%4];\n}\n"
               : "+r"(r[0]), "+r"(r[1]), "+r"(r[2]), "+r"(r[3]) : "r"(a), "r"((uint32_t)on) : "memory");
}
__device__ __forceinline__ void stage_sum(const float* acc, const uint32_t* add, uint32_t addr) {
#pragma unroll
  for (int j = 0; j < 4; j++) {
    uint32_t p[4];
#pragma unroll
    for (int i = 0; i < 4; i++) p[i] = add_bf16x2(add[4 * j + i], pack_bf16(acc[8 * j + 2 * i], acc[8 * j + 2 * i + 1]));
    sts128(addr + j * 512, p);
  }
}
__device__ __forceinline__ void lag_sync(int wg) {
  if (wg == 1) asm volatile("bar.sync 4, 256;" ::: "memory");
}
__device__ __forceinline__ void lag_arrive(int wg) {
  if (wg == 0) asm volatile("bar.arrive 4, 256;" ::: "memory");
}

__device__ __forceinline__ void add_packed(uint32_t* d, uint32_t a0, uint32_t a1) {
#pragma unroll
  for (int j = 0; j < 4; j++) {
    uint32_t v[4];
    lds128(d + 4 * j, a0 + j * 512);
    lds128(v, a1 + j * 512);
#pragma unroll
    for (int i = 0; i < 4; i++) d[4 * j + i] = add_bf16x2(d[4 * j + i], v[i]);
  }
}

template <int T, typename Fn>
__device__ __forceinline__ void step64(float (&acc)[32], const uint32_t (&A)[144], uint32_t sb, uint64_t desc0, Ring& ring,
                                       int wg, int lane, Fn&& side) {
  uint32_t prev = 0;
  ring.slot = __shfl_sync(~0u, ring.slot, 0);
#pragma unroll
  for (int st = 0; st < 5; st++) {
    mbar_wait(sb + B_FULL + 8 * ring.slot, ring.phase);
    const uint64_t db = desc0 + (ring.off() >> 4);
    if (st == 5 - LAG3) lag_sync(wg);
    WG_FENCE();
#pragma unroll
    for (int k = 0; k < (st < 4 ? 8 : 4); k++) wgmma_rs<64, 1>(acc, &A[(st * 8 + k) * 4], db + k * 128, st + k);
    WG_COMMIT();
    if (st == 4) lag_arrive(wg);
    if (st > 0 && T * 5 + st - 1 < 15 - NS) {
      WG_WAIT(1);
      release_slot(sb, prev, lane);
    }
    prev = ring.slot;
    ring.next();
    side(st);
  }
  WG_WAIT(0);
  if (T * 5 + 4 < 15 - NS) release_slot(sb, prev, lane);
}

__device__ __forceinline__ void ffn_consumer(uint32_t sb, Scratch* g, int warp, int r, int s, __nv_bfloat16* __restrict__ out) {
  const int tid = fresh_tid(), wg = warp >> 2, w = warp & 3, lane = tid & 31;
  const uint32_t stash = OFF_STASH + wg * STASH_STRIDE;
  const uint32_t priv = sb + stash + w * 2048 + lane * 16;
  uint32_t A[144];
  float rs0, rs1;
  const uint32_t tr_off = ((lane >> 4) * 8 + (lane & 7)) * 128 + (((2 * w + ((lane >> 3) & 1)) ^ (lane & 7)) << 4);
  {
    float st[4][4];
#pragma unroll
    for (int i = 0; i < 4; i++) st[i][0] = st[i][1] = st[i][2] = st[i][3] = 0.f;
    const uint32_t ones[2] = {0x3f803f80u, 0x3f803f80u};
    const bool up = s & 1;
#pragma unroll
    for (int kb = 0; kb < 9; kb++) {
      if (kb == 0 || (kb & 1)) mbar_wait(sb + B_H + 8 * (wg * 5 + (kb + 1) / 2), 0);
      const uint32_t box = sb + (kb ? stash + (kb - 1) * BOX : (NS - 1) * SLOT + wg * BOX) + tr_off;
#pragma unroll
      for (int k = 0; k < 4; k++) {
        uint32_t* a = &A[(kb * 4 + k) * 4];
        ldsm4t(a, box + k * 2048);
        const uint32_t bt[2] = {up ? a[1] : a[0], up ? a[3] : a[2]};
        mma_bf16(st[k & 1], a[0], a[1], a[2], a[3], ones);
        mma_bf16(st[2 + (k & 1)], a[0], a[1], a[2], a[3], bt);
      }
      if (kb == 2) release_slot(sb, NS - 1, lane);
      if (kb == 0) STAMP(24 + wg);
      if (kb == 8) STAMP(26 + wg);
    }
    rs0 = (st[0][0] + st[1][0]) * (1.f / D);
    rs1 = (st[0][2] + st[1][2]) * (1.f / D);
    const float qe = up ? st[2][2] + st[3][2] : st[2][0] + st[3][0], qo = up ? st[2][3] + st[3][3] : st[2][1] + st[3][1];
    if ((lane & 3) == (lane >> 3)) {
      const uint32_t q = __float_as_uint((lane & 4) ? qo : qe), off = OFF_VAR + 64 * warp + 32 * up + (lane & 28);
      const uint32_t pb = mapa(sb, up ^ 1);
      sts32(sb + off, q);
      asm volatile("st.async.weak.shared::cluster.mbarrier::complete_tx::bytes.b32 [%0], %1, [%2];"
                   ::"r"(pb + off), "r"(q), "r"(pb + B_VAR + 8 * wg) : "memory");
    }
    if (wg == 1) asm volatile("bar.arrive 6, 256;" ::: "memory");
    const uint32_t mm0 = pack_bf16(rs0, rs0), mm1 = pack_bf16(rs1, rs1);
#pragma unroll
    for (int i = 0; i < 144; i++) A[i] = sub_bf16x2(A[i], (i & 1) ? mm1 : mm0);
  }
  if (wg == 0) asm volatile("bar.sync 6, 256;" ::: "memory");
  STAMP(2 + wg);

  Ring ring{0, 0};
  const uint64_t desc0 = bdesc(sb);
#pragma unroll 1
  for (int step = 0; step < 12; step++) {
    float acc[64];
    uint32_t prev = 0;
#pragma unroll
    for (int kb = 0; kb < 9; kb++) {
      mbar_wait(sb + B_FULL + 8 * ring.slot, ring.phase);
      const uint64_t db = desc0 + (ring.off() >> 4);
      if (LAG1 == LAG2) {
        if (kb == 9 - LAG1) lag_sync(wg);
      } else {
        if (kb == 9 - LAG1 && step < 9) lag_sync(wg);
        if (kb == 9 - LAG2 && step >= 9) lag_sync(wg);
      }
      WG_FENCE();
#pragma unroll
      for (int k = 0; k < 4; k++) wgmma_rs<128, 1>(acc, &A[(kb * 4 + k) * 4], db + k * 128, kb + k);
      WG_COMMIT();
      if (kb == 8) lag_arrive(wg);
      if (kb == 0 && step > 9) stage_done(sb + B_SF + 8 * (wg * 5 + step - 10), lane);
      if (kb > 0) {
        WG_WAIT(1);
        release_slot(sb, prev, lane);
#pragma unroll
        for (int j = 0; j < 4; j++) lds128_if(&A[16 * (kb - 1) + 4 * j], priv + (kb - 1) * BOX + j * 512, step == 8);
      }
      prev = ring.slot;
      ring.next();
    }
    if (step == 0) {
      mbar_wait(sb + B_VAR + 8 * wg, 0);
      wg_bar(wg);
      const uint32_t va = sb + OFF_VAR + 64 * warp + (lane & 28);
      rs0 = ln_rstd(fmaxf(__uint_as_float(lds32(va)) * (1.f / D) - rs0 * rs0, 0.f));
      rs1 = ln_rstd(fmaxf(__uint_as_float(lds32(va + 32)) * (1.f / D) - rs1 * rs1, 0.f));
      if (warp == s && (lane & 3) == 0) {
        sts32(sb + OFF_MISC + 160 + lane, __float_as_uint(rs0));
        sts32(sb + OFF_MISC + 192 + lane, __float_as_uint(rs1));
      }
    }
    if (step > 9) {
      mbar_wait(sb + B_XIN + 8 * (wg * 4 + step - 10), 0);
      mbar_wait(sb + B_SE + 8 * (wg * 3 + step - 10), 0);
    }
    WG_WAIT(0);
    release_slot(sb, prev, lane);
    if (step < 9) {
      uint32_t hp[16];
      const float c0 = 0.5f * rs0, c1 = 0.5f * rs1;
#pragma unroll
      for (int i = 0; i < 16; i++) {
        const float c = (i & 1) ? c1 : c0;
        const float g0 = acc[2 * i] * c, g1 = acc[2 * i + 1] * c;
        const float h0 = fmaf(g0, tanh_hw(g0), g0) * acc[32 + 2 * i];
        const float h1 = fmaf(g1, tanh_hw(g1), g1) * acc[33 + 2 * i];
        hp[i] = pack_bf16(h0, h1);
      }
      if (step < 8) {
#pragma unroll
        for (int j = 0; j < 4; j++) sts128(priv + step * BOX + j * 512, &hp[4 * j]);
      } else {
#pragma unroll
        for (int i = 0; i < 16; i++) A[128 + i] = hp[i];
        STAMP(4 + wg);
      }
    } else {
      const int e = step - 9;
      stage_partial(acc, priv + (2 + (e & 1)) * BOX);
      uint32_t xin[16];
#pragma unroll
      for (int j = 0; j < 4; j++) lds128(&xin[4 * j], e > 0 ? priv + ((e - 1) & 1) * BOX + j * 512 : sb + OFF_ZERO);
      stage_sum(acc + 32, xin, priv + 4 * BOX);
    }
  }
  STAMP(6 + wg);

  float acc[32];
  uint32_t pa[16], o8[2];
  step64<0>(acc, A, sb, desc0, ring, wg, lane, [&](int st) {
    if (st == 0) stage_done(sb + B_SF + 8 * (wg * 5 + 2), lane);
    if (st == 4) {
      mbar_wait(sb + B_XIN + 8 * (wg * 4 + 2), 0);
#pragma unroll
      for (int j = 0; j < 4; j++) lds128(&pa[4 * j], priv + j * 512);
    }
  });
  stage_sum(acc, pa, priv + 3 * BOX);
  stage_done(sb + B_SF + 8 * (wg * 5 + 3), lane);
  STAMPC(tid == 0, 12);
  step64<1>(acc, A, sb, desc0, ring, wg, lane, [&](int st) {
    if (st == B8ST) {
      const int t = fresh_tid(), d = 16 * (t >> 6) + 8 * (t & 1) + (t & 6), l = (t >> 3) & 7;
      mbar_wait(sb + B_B8, 0);
      float v[4] = {0.f, 0.f, 0.f, 0.f};
#pragma unroll
      for (int i = 0; i < 8; i++) {
        uint32_t q[2];
        lds64(q, sb + OFF_STASH + (i >> 2) * STASH_STRIDE + 6 * BOX + (i & 3) * 2048 + 8 * t);
        v[0] += bf_lo(q[0]); v[1] += bf_hi(q[0]);
        v[2] += bf_lo(q[1]); v[3] += bf_hi(q[1]);
      }
#pragma unroll
      for (int i = 0; i < 4; i++) {
        const int dd = d + (i & 1);
        const uint32_t h = lds16(sb + OFF_STASH + 7 * BOX + dd * 128 + (((2 * (s & 3) + (i >> 1)) ^ (dd & 7)) << 4) + 2 * l);
        v[i] = fmaf(v[i], __uint_as_float(lds32(sb + OFF_MISC + 160 + 32 * (i >> 1) + 4 * l)), bf_lo(h));
      }
      o8[0] = pack_bf16(v[0], v[1]);
      o8[1] = pack_bf16(v[2], v[3]);
      stage_done(sb + B_CV + 16, lane);
    }
    if (st == 3) mbar_wait(sb + B_SE + 8 * (wg * 3 + 2), 0);
  });
  stage_partial(acc, priv + 4 * BOX);
  stage_done(sb + B_SF + 8 * (wg * 5 + 4), lane);
  STAMPC(tid == 0, 13);
  step64<2>(acc, A, sb, desc0, ring, wg, lane, [&](int st) {
    if (st == 1) {
      const int t = fresh_tid(), row = (s >> 2) * 1024 + r * 64 + (s & 3) * 16 + ((t >> 3) & 7);
      uint32_t* o = reinterpret_cast<uint32_t*>(out + row * D + 512 + 16 * (t >> 6) + 8 * (t & 1) + (t & 6));
      o[0] = o8[0];
      o[4 * D] = o8[1];
      mbar_wait(sb + B_LIN + 8 * (wg * 2), 0);
    }
    if (st == XST) {
      mbar_wait(sb + B_XIN + 8 * (wg * 4 + 3), 0);
      add_packed(pa, priv + 5 * BOX, priv + BOX);
    }
    if (st == 4) {
      uint32_t pb[16];
      mbar_wait(sb + B_LIN + 8 * (wg * 2 + 1), 0);
      add_packed(pb, priv + 6 * BOX, priv);
#pragma unroll
      for (int i = 0; i < 16; i++) pa[i] = add_bf16x2(pa[i], pb[i]);
    }
  });
  STAMP(8 + wg);
  const uint32_t ob = sb + stash + 5 * BOX + w * 2048;
  __syncwarp();
#pragma unroll
  for (int i = 0; i < 4; i++) {
    uint32_t p[4];
    ldsm4t(p, sb + stash + 7 * BOX + tr_off + i * 2048);
#pragma unroll
    for (int j = 0; j < 4; j++) {
      const float rr = (j & 1) ? rs1 : rs0;
      const float lo = acc[8 * i + 2 * j] + bf_lo(pa[4 * i + j]), hi = acc[8 * i + 2 * j + 1] + bf_hi(pa[4 * i + j]);
      p[j] = add_bf16x2(p[j], pack_bf16(lo * rr, hi * rr));
    }
    stsm4(ob + (lane & 15) * 128 + (((2 * i + (lane >> 4)) ^ (lane & 7)) << 4), p);
  }
  __syncwarp();
  __nv_bfloat16* o = out + (wg * 1024 + r * 64 + w * 16 + (lane >> 3)) * D + s * 64 + (lane & 7) * 8;
#pragma unroll
  for (int i = 0; i < 4; i++) {
    const int row = 4 * i + (lane >> 3);
    uint32_t v[4];
    lds128(v, ob + row * 128 + (((lane & 7) ^ (row & 7)) << 4));
    *reinterpret_cast<uint4*>(o + 4 * i * D) = make_uint4(v[0], v[1], v[2], v[3]);
  }
  STAMP(10 + wg);
}

__device__ __forceinline__ void load_stage(uint32_t sb, const Ring& ring, int it, int s, const CUtensorMap* w1,
                                           const CUtensorMap* w3, const CUtensorMap* w2) {
  const uint32_t bar = sb + B_FULL + 8 * ring.slot, dst = sb + ring.off();
  if (it < 81) {
    const int step = it / 9, kb = it - step * 9;
    mbar_expect(bar, SLOT);
    tma2d(dst, w1, s * 576 + step * 64, kb * 64, bar);
    tma2d(dst + BOX, w3, s * 576 + step * 64, kb * 64, bar);
  } else if (it < 108) {
    const int e = (it - 81) / 9, kb = it - 81 - e * 9;
    mbar_expect(bar, SLOT);
    tma2d(dst, w2, (((s + 2 * e + 2) & 7) ^ 1) * 64, s * 576 + kb * 64, bar);
    tma2d(dst + BOX, w2, (e == 0 ? 8 : (s + 2 * e) & 7) * 64, s * 576 + kb * 64, bar);
  } else {
    const int e = (it - 108) / 5, st = it - 108 - e * 5;
    const int blk = e == 0 ? (s + 6) & 7 : e == 1 ? s ^ 1 : s;
    mbar_expect(bar, st < 4 ? SLOT : BOX);
    tma2d(dst, w2, blk * 64, s * 576 + st * 128, bar);
    if (st < 4) tma2d(dst + BOX, w2, blk * 64, s * 576 + st * 128 + 64, bar);
  }
}

__device__ __forceinline__ void ffn_producer(uint32_t sb, int s, int first, const CUtensorMap* w1, const CUtensorMap* w3,
                                             const CUtensorMap* w2) {
  Ring ring{(uint32_t)first, 1};
  mbar_wait(sb + B_CV + 8, 0);
#pragma unroll 1
  for (int it = first; it < 123; it++) {
    mbar_wait(sb + B_EMPTY + 8 * ring.slot, ring.slot == NS - 1 ? ring.phase ^ 1 : ring.phase);
    if (elect_one()) load_stage(sb, ring, it, s, w1, w3, w2);
    __syncwarp();
    ring.next();
  }
  const uint32_t pb = mapa(sb, (s & 1) ^ 1);
#pragma unroll 1
  for (int wg = 0; wg < 2; wg++) {
    const uint32_t stash = OFF_STASH + wg * STASH_STRIDE;
    mbar_wait(sb + B_SF + 8 * (wg * 5 + 4), 0);
    if (elect_one()) bulk_peer(pb + stash + BOX, sb + stash + 4 * BOX, BOX, pb + B_XIN + 8 * (wg * 4 + 3));
    __syncwarp();
  }
}

__device__ __forceinline__ void ffn_sender(uint32_t sb, Scratch* g, int r, int s, int wg) {
  const uint32_t stash = OFF_STASH + wg * STASH_STRIDE, pb = mapa(sb, (s & 1) ^ 1);
  mbar_wait(sb + B_CV + 8 * wg, 0);
  STAMPC(1, 58 + wg);
  if (elect_one()) {
    asm volatile("fence.release.gpu;" ::: "memory");
    red_add(&g->epoch[32 * wg], 1);
  }
  __syncwarp();
#pragma unroll 1
  for (int e = 0; e < 4; e++) {
    mbar_wait(sb + B_SF + 8 * (wg * 5 + e), 0);
    STAMPC(e == 3 && wg == 0, 62);
    if (e == 0) {
      if (elect_one()) mbar_arrive_cluster(pb + B_PRDY + 8 * wg);
      __syncwarp();
      mbar_wait(sb + B_PRDY + 8 * wg, 0);
    }
    if (elect_one()) {
      if (e < 3) bulk_peer(pb + stash + (e & 1) * BOX, sb + stash + (2 + (e & 1)) * BOX, BOX, pb + B_XIN + 8 * (wg * 4 + e));
      const int idx = ((r * 8 + ((s + 2 * e) & 7)) * 3 + e - 1) * 2 + wg;
      uint4* dst = e == 0 ? &g->part8[((r * 8 + s) * 2 + wg) * 512] : &g->part[idx * 512];
#pragma unroll 1
      for (uint32_t q = 0, n = e == 3 ? BOX : PACE; q < BOX; q += n) {
        bulk_store(dst + (q >> 4), sb + stash + (e == 3 ? 3 : 4) * BOX + q, n);
        asm volatile("cp.async.bulk.commit_group;" ::: "memory");
        asm volatile("cp.async.bulk.wait_group.read 0;" ::: "memory");
      }
      if (e < 3) mbar_arrive(sb + B_SE + 8 * (wg * 3 + e));
      if (e != 2) {
        asm volatile("cp.async.bulk.wait_group 0;" ::: "memory");
        STAMPC(e == 3 && wg == 0, 63);
        asm volatile("fence.release.gpu;" ::: "memory");
        if (e == 0) {
#pragma unroll
          for (int q = 0; q < 4; q++) red_add(&g->flag8[r * 8 + wg * 4 + q], 1);
        } else {
          if (e == 3) red_add(&g->flag[((r * 8 + ((s + 4) & 7)) * 3 + 1) * 2 + wg], 1);
          red_add(&g->flag[idx], 1);
        }

      }
    }
    __syncwarp();
  }
  mbar_wait(sb + B_XIN + 8 * (wg * 4 + 3), 0);
  if (elect_one()) mbar_arrive_cluster(pb + B_DONE + 8 * wg);
  __syncwarp();
  mbar_wait(sb + B_DONE + 8 * wg, 0);
}

__device__ __forceinline__ void ffn_receiver(uint32_t sb, Scratch* g, int c, int r, int s, const CUtensorMap* ht,
                                             const CUtensorMap* ht3) {
  const int lane = fresh_tid() & 31;
#pragma unroll 1
  for (int h = 0; h < 2; h++) {
    wait_flag(&g->epoch[32 * h], (lds32(sb + OFF_MISC + 152) & ~127u) + 128);
    STAMPC(lane == 0 && h == 0, 31);
    mbar_wait(sb + B_CV + 8, 0);
    STAMPC(lane == 0, h ? 23 : 1);
    if (elect_one()) {
      asm volatile("fence.proxy.async.global;" ::: "memory");
      tma2d(sb + (NS - 1) * SLOT + h * BOX, ht, h * 1024 + r * 64, 0, sb + B_H + 40 * h);
#pragma unroll
      for (int i = 0; i < 4; i++)
        tma2d(sb + OFF_STASH + h * STASH_STRIDE + i * SLOT, ht3, h * 1024 + r * 64, 64 + 128 * i, sb + B_H + 40 * h + 8 + 8 * i);
    }
    __syncwarp();
  }
  if (lane < 6) g->stats[(lane >> 1) * 256 + 2 * c + (lane & 1)] = make_uint4(0, 0, 0, 0);
  mbar_wait(sb + B_SF, 0);
  mbar_wait(sb + B_SF + 40, 0);
  wait_flag(&g->flag8[r * 8 + s], 8);
  __syncwarp();
  if (elect_one()) {
    g->flag8[r * 8 + s] = 0;
    asm volatile("fence.proxy.async.global;" ::: "memory");
    tma2d(sb + OFF_STASH + 7 * BOX, ht, (s >> 2) * 1024 + r * 64, 512, sb + B_B8);
#pragma unroll 1
    for (int i = 0; i < 8; i++)
      bulk_load(sb + OFF_STASH + (i >> 2) * STASH_STRIDE + 6 * BOX + (i & 3) * 2048, &g->part8[(r * 8 + i) * 1024 + s * 128],
                2048, sb + B_B8);
  }
  __syncwarp();
  const int base = (r * 8 + s) * 6;
#pragma unroll 1
  for (int late = 0; late < 2; late++) {
    if (late) {
      mbar_wait(sb + B_CV + 16, 0);
      if (elect_one()) {
        tma2d(sb + OFF_STASH + 7 * BOX, ht, r * 64, s * 64, sb + B_LIN + 8);
        tma2d(sb + OFF_STASH + STASH_STRIDE + 7 * BOX, ht, 1024 + r * 64, s * 64, sb + B_LIN + 24);
      }
      __syncwarp();
    }
    uint32_t todo = late ? 0x3c : 0x03;
#pragma unroll 1
    for (uint32_t spins = 0; todo; spins++) {
      if (spins > SPIN_LIMIT) __trap();
      uint32_t ready = __ballot_sync(~0u, ((todo >> lane) & 1) && ld_acquire(&g->flag[base + lane]) != 0);
      __syncwarp();
      todo &= ~ready;
#pragma unroll 1
      for (; ready; ready &= ready - 1) {
        const int i = __ffs(ready) - 1, wg = i & 1, j = i >> 1;
        if (elect_one()) {
          asm volatile("fence.proxy.async.global;" ::: "memory");
          bulk_load(sb + OFF_STASH + wg * STASH_STRIDE + (j == 2 ? 0 : 5 + j) * BOX, &g->part[(base + i) * 512], BOX,
                    sb + B_LIN + 8 * (wg * 2 + late));
        }
        __syncwarp();
      }
    }
  }
  if (lane < 6) g->flag[base + lane] = 0;

}

__global__ void __launch_bounds__(384, 1)
fused_kernel(const __grid_constant__ SsmParams p, __nv_bfloat16* __restrict__ out,
             const __grid_constant__ CUtensorMap tm_w1, const __grid_constant__ CUtensorMap tm_w3,
             const __grid_constant__ CUtensorMap tm_w2, const __grid_constant__ CUtensorMap tm_ht,
             const __grid_constant__ CUtensorMap tm_ht3, const __grid_constant__ CUtensorMap tm_x) {
  extern __shared__ __align__(1024) uint8_t smem[];
  uint32_t sb = (uint32_t)__cvta_generic_to_shared(smem);
  asm volatile("" : "+r"(sb));
  const int c = blockIdx.x, cl = c >> 1, rank = c & 1, tid = threadIdx.x, warp = warp_index(), wg = warp >> 2;
  const int s = ((cl & 1) * 2 + ((cl >> 3) & 1)) * 2 + rank, r = ((cl >> 1) & 3) * 4 + (cl >> 4);
  STAMPC(tid == 0, 0);
  Scratch* const g = p.g;
  unsigned target = 0;
  int first = 0;
  const int w = warp & 3, lane = tid & 31;
  const int ch0 = 9 * cl + 5 * rank;
  ModeIn in;
  uint4 xv[9];
  uint32_t t0;
  asm volatile("mov.u32 %0, %clock;" : "=r"(t0));
  if (wg < 2) {
    in = load_modes(p, ch0 + (warp >> 1), tid & 63);
  } else {
    const uint4* xr = reinterpret_cast<const uint4*>(p.x) + (16 * c + ((tid & 127) >> 3)) * (D / 8) + (tid & 7);
    for (uint32_t now = t0; now - t0 < XDELAY;) asm volatile("mov.u32 %0, %clock;" : "=r"(now));
#pragma unroll
    for (int i = 0; i < 9; i++)
      asm volatile("ld.global.nc.v4.u32 {%0,%1,%2,%3}, [%4];"
                   : "=r"(xv[i].x), "=r"(xv[i].y), "=r"(xv[i].z), "=r"(xv[i].w) : "l"(xr + 8 * i));
    if (rank == 1) in = load_modes(p, ch0 - 1, tid & 63);
  }
  const uint32_t dsk = ldg16(p.dskip + min(ch0 + (tid & 7), D - 1));
  if (tid == 8) asm volatile("ld.relaxed.gpu.global.u32 %0, [%1];" : "=r"(target) : "l"(&g->epoch[32]) : "memory");
  STAMP(38 + wg);
  if (warp == 9) {
    const uint32_t z[4] = {0, 0, 0, 0};
    sts128(sb + OFF_ZERO, z);
#pragma unroll 1
    for (int i = 0; i < 5; i++)
    {
      if (lane < 26) sts128(sb + (lane < 24 ? OFF_U + i * U_PITCH : OFF_PK - 384 + i * PK_PITCH) + lane * 16, z);
    }
  }
  if (warp == 8 && elect_one()) {
    asm volatile("prefetch.tensormap [%0];" ::"l"(&tm_x) : "memory");
#pragma unroll
    for (uint32_t b = B_G; b < B_END; b += 8) mbar_init(sb + b, b == B_UX ? 2 : b < B_SF ? 1 : b < B_EMPTY ? 4 : 8);
#pragma unroll
    for (uint32_t b = B_G; b < B_FULL; b += 8)
      mbar_expect(sb + b, b < B_PK ? 2 * BOX : b < B_LIN ? BOX : b < B_H ? ((b - B_LIN) & 8 ? 3 : 1) * BOX : b < B_UX ? ((b - B_H) % 40 ? 2 : 1) * BOX : b < B_VAR ? 5 * L : b < B_B8 ? 128 : 3 * BOX);
    asm volatile("fence.mbarrier_init.release.cluster;" ::: "memory");
    for (uint32_t now = t0; now - t0 < GDELAY;) asm volatile("mov.u32 %0, %clock;" : "=r"(now));
#pragma unroll
    for (int i = 0; i < 2; i++)
      asm volatile(
          "cp.async.bulk.tensor.5d.shared::cluster.global.mbarrier::complete_tx::bytes [%0], [%1, {%3, %4, %4, %4, %5}], [%2];"
          ::"r"(sb + OFF_G + i * SLOT), "l"(&tm_x), "r"(sb + B_G + 8 * i), "r"((9 * cl) & ~7), "r"(0), "r"(32 * rank + 16 * i)
          : "memory");
  }
  __syncwarp();
  asm volatile("barrier.cluster.arrive.relaxed.aligned;" ::: "memory");
  STAMPC(tid == 256, 41);
  if (wg == 2) {
    ln1_stats(sb, g, c, xv);
    STAMP(14);
    asm volatile("barrier.cluster.wait.aligned;" ::: "memory");
    x_transpose(sb, c, w);
    STAMP(18);
  }
  const int ntask = wg < 2 ? 2 : 1 - rank;
  if (wg < 2 || rank == 1) {
    float acc[6][4];
#pragma unroll
    for (int i = 0; i < 6; i++) acc[i][0] = acc[i][1] = acc[i][2] = acc[i][3] = 0.f;
#pragma unroll 1
    for (int k = wg >> 1; k < 2; k++) {
      kgen_modes(sb + OFF_WS + wg * WS_BYTES + w * WS_WARP, in, (wg == 2 ? w >> 1 : k) ? 0x3244 : 0x1044, acc);
      STAMP(46 + wg * 2 + k);
    }
    uint32_t st[12];
    if (wg < 2) asm volatile("barrier.cluster.wait.aligned;" ::: "memory");
    kgen_finish(sb, g, wg, acc, st);
    STAMP(52 + wg);
    if (wg < 2) {
      if (tid < 9) sts32(sb + OFF_MISC + 120 + 4 * tid, tid < 8 ? dsk * 0x10001u : target);
      ln1_apply(sb, g, st);
      asm volatile("fence.proxy.async.shared::cta;\nbar.arrive 6, 384;\nbar.sync 4, 256;" ::: "memory");
    } else {
      asm volatile("fence.proxy.async.shared::cta;" ::: "memory");
      wg_bar(2);
      if (w == 2 && elect_one()) {
        const uint32_t pb = mapa(sb, 0), off = OFF_PK + 4 * PK_PITCH + 32;
        bulk_peer(pb + off, sb + off, BOX, pb + B_PK);
      }
      __syncwarp();
    }
  }
  if (wg == 2) {
    asm volatile("bar.sync 6, 384;" ::: "memory");
    mbar_wait(sb + B_UX, 0);
    if (w == 0 && elect_one()) {
#pragma unroll 1
      for (int i = 0; i < EARLY; i++) {
        const uint32_t bar = sb + B_FULL + 8 * i, dst = sb + i * SLOT;
        mbar_expect(bar, SLOT);
        tma2d(dst, &tm_w1, s * 576, i * 64, bar);
        tma2d(dst + BOX, &tm_w3, s * 576, i * 64, bar);
      }
      asm volatile("prefetch.tensormap [%0];" ::"l"(&tm_ht) : "memory");
      asm volatile("prefetch.tensormap [%0];" ::"l"(&tm_ht3) : "memory");
    }
    if (w == 1 && lane < 9) {
      const __nv_bfloat16* wp = (lane < 3 ? p.w1 : lane < 6 ? p.w3 : p.w2) + c * 20736 + (lane % 3) * 6912;
      asm volatile("cp.async.bulk.prefetch.L2.global [%0], %1;" ::"l"(wp), "r"(13824) : "memory");
    }
    __syncwarp();
    STAMP(55);
  }
  first = EARLY;
  STAMPC(tid == 0, 19);
#pragma unroll 1
  for (int k = 0; k < ntask; k++) {
    const int local = wg == 2 ? 3 : 2 * wg + k + (wg & k & (rank ^ 1));
    if (local == 4) mbar_wait(sb + B_PK, 0);
    conv_task(sb, g, wg, w, local, ch0 + local, k);
  }
  STAMP(20 + wg);
  asm volatile("fence.proxy.async.shared::cta;" ::: "memory");
  __syncwarp();
  if (wg == 2) wg_bar(2);
  else if (elect_one()) mbar_arrive(sb + B_CV + 8);
  __syncwarp();

  if (wg < 2) {
    asm volatile("setmaxnreg.inc.sync.aligned.u32 240;");
    ffn_consumer(sb, g, warp, r, s, out);
  } else {
    asm volatile("setmaxnreg.dec.sync.aligned.u32 24;");
    const int hw = warp & 3;
    if (hw == 0) ffn_producer(sb, s, first, &tm_w1, &tm_w3, &tm_w2);
    else if (hw < 3) ffn_sender(sb, g, r, s, hw - 1);
    else ffn_receiver(sb, g, c, r, s, &tm_ht, &tm_ht3);
  }
}

typedef CUresult (*EncodeFn)(CUtensorMap*, CUtensorMapDataType, cuuint32_t, void*, const cuuint64_t*, const cuuint64_t*,
                             const cuuint32_t*, const cuuint32_t*, CUtensorMapInterleave, CUtensorMapSwizzle,
                             CUtensorMapL2promotion, CUtensorMapFloatOOBfill);

void make_map(EncodeFn enc, CUtensorMap* m, void* p, uint64_t cols, uint64_t rows, uint32_t box_rows = 64) {
  cuuint64_t dims[2] = {cols, rows}, strides[1] = {cols * 2};
  cuuint32_t box[2] = {64, box_rows}, es[2] = {1, 1};
  enc(m, CU_TENSOR_MAP_DATA_TYPE_BFLOAT16, 2, p, dims, strides, box, es, CU_TENSOR_MAP_INTERLEAVE_NONE,
      CU_TENSOR_MAP_SWIZZLE_128B, CU_TENSOR_MAP_L2_PROMOTION_L2_128B, CU_TENSOR_MAP_FLOAT_OOB_FILL_NONE);
}

}

extern "C" void kernel_launch(void* const* d_in, const int* in_sizes, int n_in, void* d_out, int out_size) {
  typedef const __nv_bfloat16* P;
  void* fn = nullptr;
  cudaDriverEntryPointQueryResult qr;
  cudaGetDriverEntryPoint("cuTensorMapEncodeTiled", &fn, cudaEnableDefault, &qr);
  EncodeFn enc = (EncodeFn)fn;
  void* hT = nullptr;
  cudaGetSymbolAddress(&hT, g_scratch);
  CUtensorMap m1, m3, m2, mh, mh3, mx;
  make_map(enc, &m1, d_in[10], F, D);
  make_map(enc, &m3, d_in[11], F, D);
  make_map(enc, &m2, d_in[12], D, F);
  make_map(enc, &mh, hT, L, D);
  make_map(enc, &mh3, hT, L, D, 128);
  {
    cuuint64_t dims[5] = {D, 2, 4, 4, 64}, strides[4] = {D * 2, D * 16, D * 4, D * 64};
    cuuint32_t box[5] = {16, 2, 4, 4, 16}, es[5] = {1, 1, 1, 1, 1};
    enc(&mx, CU_TENSOR_MAP_DATA_TYPE_BFLOAT16, 5, d_in[0], dims, strides, box, es, CU_TENSOR_MAP_INTERLEAVE_NONE,
        CU_TENSOR_MAP_SWIZZLE_32B, CU_TENSOR_MAP_L2_PROMOTION_L2_128B, CU_TENSOR_MAP_FLOAT_OOB_FILL_NONE);
  }
  SsmParams p = {(P)d_in[0], (P)d_in[1], (P)d_in[2], (P)d_in[3], (P)d_in[4], (P)d_in[5],
                 (P)d_in[6], (P)d_in[7], (P)d_in[8], (P)d_in[10], (P)d_in[11], (P)d_in[12], (Scratch*)hT};
  cudaFuncSetAttribute(fused_kernel, cudaFuncAttributeMaxDynamicSharedMemorySize, SMEM_BYTES);
  cudaLaunchConfig_t cfg = {};
  cfg.gridDim = dim3(128);
  cfg.blockDim = dim3(384);
  cfg.dynamicSmemBytes = SMEM_BYTES;
  cfg.stream = cudaStreamPerThread;
  cudaLaunchAttribute at[1];
  at[0].id = cudaLaunchAttributeClusterDimension;
  at[0].val.clusterDim.x = 2;
  at[0].val.clusterDim.y = 1;
  at[0].val.clusterDim.z = 1;
  cfg.attrs = at;
  cfg.numAttrs = 1;
  cudaLaunchKernelEx(&cfg, fused_kernel, p, (__nv_bfloat16*)d_out, m1, m3, m2, mh, mh3, mx);
}
```

```cpp
#include <cuda_runtime.h>
#include <cuda_bf16.h>
#include <cuda.h>
#include <stdint.h>

#define LAG1 4
#define LAG2 4
#define LAG3 3
#define HMC 0
#define GDELAY 1800
#define XDELAY 600
#define XST 4
#define VKB 4
#define SKB 2
#define PFN 32
#define B8ST 1
#define PACE 4096

namespace {

constexpr int L = 2048, D = 576, F = 4608, NMODE = 128;
constexpr int NS = 6;
constexpr uint32_t SLOT = 16384, BOX = 8192;
constexpr uint32_t OFF_STASH = NS * SLOT, STASH_STRIDE = 8 * BOX;
constexpr uint32_t OFF_BAR = NS * SLOT + 16 * BOX;
constexpr uint32_t B_G = OFF_BAR, B_PK = B_G + 8 * 2, B_XIN = B_PK + 8, B_LIN = B_XIN + 8 * 8, B_H = B_LIN + 8 * 4, B_UX = B_H + 8 * 10,
                   B_VAR = B_UX + 8, B_B8 = B_VAR + 16, B_FULL = B_B8 + 8, B_SE = B_FULL + 8 * NS, B_PRDY = B_SE + 8 * 6,
                   B_DONE = B_PRDY + 8 * 2, B_SF = B_DONE + 8 * 2, B_EMPTY = B_SF + 8 * 10, B_CV = B_EMPTY + 8 * NS, B_END = B_CV + 8 * 3;
constexpr uint32_t OFF_MISC = OFF_BAR + 768;
constexpr uint32_t OFF_ZERO = OFF_MISC + 224;
constexpr uint32_t OFF_VAR = OFF_BAR + 1536;
constexpr uint32_t SMEM_BYTES = OFF_VAR + 512;
constexpr uint32_t SPIN_LIMIT = 1u << 24;
static_assert(B_END <= OFF_BAR + 512, "barrier region");

constexpr uint32_t EARLY = 4;
constexpr uint32_t OFF_G = 0;
constexpr uint32_t OFF_WS = 2 * SLOT, WS_WARP = 7168, WS_KC = 4 * WS_WARP + 16, KC_PITCH = 1312, WS_BYTES = 32768;
constexpr uint32_t OFF_PART = EARLY * SLOT;
constexpr uint32_t OFF_U = OFF_WS + 3 * WS_BYTES, U_PAD = 384, U_PITCH = U_PAD + 4096;
constexpr uint32_t OFF_X = OFF_U + 5 * U_PITCH, X_PITCH = 4160;
constexpr uint32_t OFF_PK = OFF_X + 5 * X_PITCH, PK_PITCH = 8224;
constexpr uint32_t OFF_STG = OFF_PK + 5 * PK_PITCH, STG_PITCH = 2112;
static_assert(OFF_STG + 5 * STG_PITCH <= OFF_BAR, "front region");
static_assert(WS_KC + 2 * KC_PITCH <= WS_BYTES, "scratch");

struct Scratch {
  __nv_bfloat16 hT[D * L];
  uint4 part[16 * 8 * 3 * 2 * 512];
  uint4 part8[16 * 8 * 2 * 512];
  uint4 stats[3 * 256];
  unsigned flag[16 * 8 * 3 * 2];
  unsigned flag8[16 * 8];
  unsigned epoch[64];
};
__device__ __align__(1024) Scratch g_scratch;
#define STAMP(i)
#define STAMPC(c, i)

__device__ __forceinline__ int fresh_tid() {
  int t;
  asm volatile("mov.u32 %0, %tid.x;" : "=r"(t));
  return t;
}
__device__ __forceinline__ int warp_index() { return __shfl_sync(~0u, fresh_tid() >> 5, 0); }
__device__ __forceinline__ void mbar_init(uint32_t b, uint32_t c) {
  asm volatile("mbarrier.init.shared::cta.b64 [%0], %1;" ::"r"(b), "r"(c));
}
__device__ __forceinline__ void mbar_expect(uint32_t b, uint32_t n) {
  asm volatile("mbarrier.arrive.expect_tx.shared::cta.b64 _, [%0], %1;" ::"r"(b), "r"(n) : "memory");
}
__device__ __forceinline__ void mbar_arrive(uint32_t b) {
  asm volatile("mbarrier.arrive.shared::cta.b64 _, [%0];" ::"r"(b) : "memory");
}
__device__ __forceinline__ void mbar_arrive_cluster(uint32_t b) {
  asm volatile("mbarrier.arrive.shared::cluster.b64 _, [%0];" ::"r"(b) : "memory");
}
__device__ __forceinline__ void mbar_wait(uint32_t b, uint32_t parity) {
  asm volatile(
      "{\n.reg .pred p;\n.reg .u32 c;\nmov.u32 c, 0;\n"
      "WAIT:\nmbarrier.try_wait.parity.shared::cta.b64 p, [%0], %1;\n@p bra DONE;\n"
      "add.u32 c, c, 1;\nsetp.lt.u32 p, c, %2;\n@p bra WAIT;\ntrap;\nDONE:\n}\n" ::"r"(b), "r"(parity), "n"(SPIN_LIMIT) : "memory");
}
__device__ __forceinline__ bool elect_one() {
  uint32_t p;
  asm volatile("{\n.reg .pred p;\nelect.sync _|p, 0xffffffff;\nselp.u32 %0, 1, 0, p;\n}\n" : "=r"(p));
  return p != 0;
}
__device__ __forceinline__ void tma2d(uint32_t dst, const CUtensorMap* m, int c0, int c1, uint32_t bar) {
  asm volatile("cp.async.bulk.tensor.2d.shared::cluster.global.mbarrier::complete_tx::bytes [%0], [%1, {%3, %4}], [%2];"
               ::"r"(dst), "l"(m), "r"(bar), "r"(c0), "r"(c1) : "memory");
}
__device__ __forceinline__ void tma2d_mc(uint32_t dst, const CUtensorMap* m, int c0, int c1, uint32_t bar) {
  asm volatile(
      "cp.async.bulk.tensor.2d.shared::cluster.global.mbarrier::complete_tx::bytes.multicast::cluster [%0], [%1, {%3, %4}], [%2], %5;"
      ::"r"(dst), "l"(m), "r"(bar), "r"(c0), "r"(c1), "h"((uint16_t)3) : "memory");
}
__device__ __forceinline__ void bulk_load(uint32_t dst, const void* src, uint32_t bytes, uint32_t bar) {
  asm volatile("cp.async.bulk.shared::cluster.global.mbarrier::complete_tx::bytes [%0], [%1], %2, [%3];"
               ::"r"(dst), "l"(src), "r"(bytes), "r"(bar) : "memory");
}
__device__ __forceinline__ void bulk_store(void* dst, uint32_t src, uint32_t bytes) {
  asm volatile("cp.async.bulk.global.shared::cta.bulk_group [%0], [%1], %2;" ::"l"(dst), "r"(src), "r"(bytes) : "memory");
}
__device__ __forceinline__ void ldsm4t(uint32_t* r, uint32_t a) {
  asm volatile("ldmatrix.sync.aligned.m8n8.x4.trans.shared.b16 {%0,%1,%2,%3}, [%4];"
               : "=r"(r[0]), "=r"(r[1]), "=r"(r[2]), "=r"(r[3]) : "r"(a) : "memory");
}
__device__ __forceinline__ void ldsm4(uint32_t* r, uint32_t a) {
  asm volatile("ldmatrix.sync.aligned.m8n8.x4.shared.b16 {%0,%1,%2,%3}, [%4];"
               : "=r"(r[0]), "=r"(r[1]), "=r"(r[2]), "=r"(r[3]) : "r"(a) : "memory");
}
__device__ __forceinline__ void ldsm2t(uint32_t* r, uint32_t a) {
  asm volatile("ldmatrix.sync.aligned.m8n8.x2.trans.shared.b16 {%0,%1}, [%2];" : "=r"(r[0]), "=r"(r[1]) : "r"(a) : "memory");
}
__device__ __forceinline__ void st_async128(uint32_t a, const uint32_t* r, uint32_t bar) {
  asm volatile("st.async.weak.shared::cluster.mbarrier::complete_tx::bytes.v4.b32 [%0], {%1,%2,%3,%4}, [%5];"
               ::"r"(a), "r"(r[0]), "r"(r[1]), "r"(r[2]), "r"(r[3]), "r"(bar) : "memory");
}
__device__ __forceinline__ void ldsm2(uint32_t* r, uint32_t a) {
  asm volatile("ldmatrix.sync.aligned.m8n8.x2.shared.b16 {%0,%1}, [%2];" : "=r"(r[0]), "=r"(r[1]) : "r"(a) : "memory");
}
__device__ __forceinline__ void ldsm1(uint32_t* r, uint32_t a) {
  asm volatile("ldmatrix.sync.aligned.m8n8.x1.shared.b16 {%0}, [%1];" : "=r"(r[0]) : "r"(a) : "memory");
}
__device__ __forceinline__ void ldc128(uint32_t* r, uint32_t a) {
  asm volatile("ld.shared::cluster.v4.b32 {%0,%1,%2,%3}, [%4];" : "=r"(r[0]), "=r"(r[1]), "=r"(r[2]), "=r"(r[3]) : "r"(a) : "memory");
}
__device__ __forceinline__ void bulk_peer(uint32_t dst, uint32_t src, uint32_t bytes, uint32_t bar) {
  asm volatile("cp.async.bulk.shared::cluster.shared::cta.mbarrier::complete_tx::bytes [%0], [%1], %2, [%3];"
               ::"r"(dst), "r"(src), "r"(bytes), "r"(bar) : "memory");
}
__device__ __forceinline__ uint32_t mapa(uint32_t a, uint32_t rank) {
  uint32_t r;
  asm("mapa.shared::cluster.u32 %0, %1, %2;" : "=r"(r) : "r"(a), "r"(rank));
  return r;
}
__device__ __forceinline__ uint32_t lds32(uint32_t a) {
  uint32_t r;
  asm volatile("ld.shared.b32 %0, [%1];" : "=r"(r) : "r"(a) : "memory");
  return r;
}
__device__ __forceinline__ uint32_t lds16(uint32_t a) {
  uint32_t r;
  asm volatile("ld.shared.u16 %0, [%1];" : "=r"(r) : "r"(a) : "memory");
  return r;
}
__device__ __forceinline__ void lds64(uint32_t* r, uint32_t a) {
  asm volatile("ld.shared.v2.b32 {%0,%1}, [%2];" : "=r"(r[0]), "=r"(r[1]) : "r"(a) : "memory");
}
__device__ __forceinline__ void sts32(uint32_t a, uint32_t v) {
  asm volatile("st.shared.b32 [%0], %1;" ::"r"(a), "r"(v) : "memory");
}
__device__ __forceinline__ void sts16(uint32_t a, uint32_t v) {
  asm volatile("st.shared.u16 [%0], %1;" ::"r"(a), "r"(v) : "memory");
}
__device__ __forceinline__ void mma_bf16(float* c, uint32_t a0, uint32_t a1, uint32_t a2, uint32_t a3, const uint32_t* b) {
  asm volatile("mma.sync.aligned.m16n8k16.row.col.f32.bf16.bf16.f32 {%0,%1,%2,%3}, {%4,%5,%6,%7}, {%8,%9}, {%0,%1,%2,%3};"
               : "+f"(c[0]), "+f"(c[1]), "+f"(c[2]), "+f"(c[3])
               : "r"(a0), "r"(a1), "r"(a2), "r"(a3), "r"(b[0]), "r"(b[1]));
}
__device__ __forceinline__ void wg_bar(int wg) { asm volatile("bar.sync %0, 128;" ::"r"(wg + 1) : "memory"); }
__device__ __forceinline__ void stsm4(uint32_t a, const uint32_t* r) {
  asm volatile("stmatrix.sync.aligned.m8n8.x4.shared.b16 [%0], {%1,%2,%3,%4};"
               ::"r"(a), "r"(r[0]), "r"(r[1]), "r"(r[2]), "r"(r[3]) : "memory");
}
__device__ __forceinline__ void sts128(uint32_t a, const uint32_t* r) {
  asm volatile("st.shared.v4.b32 [%0], {%1,%2,%3,%4};" ::"r"(a), "r"(r[0]), "r"(r[1]), "r"(r[2]), "r"(r[3]) : "memory");
}
__device__ __forceinline__ void lds128(uint32_t* r, uint32_t a) {
  asm volatile("ld.shared.v4.b32 {%0,%1,%2,%3}, [%4];" : "=r"(r[0]), "=r"(r[1]), "=r"(r[2]), "=r"(r[3]) : "r"(a) : "memory");
}
__device__ __forceinline__ uint32_t pack_bf16(float lo, float hi) {
  uint32_t r;
  asm("cvt.rn.bf16x2.f32 %0, %1, %2;" : "=r"(r) : "f"(hi), "f"(lo));
  return r;
}
__device__ __forceinline__ float bf_lo(uint32_t v) { return __uint_as_float(v << 16); }
__device__ __forceinline__ float bf_hi(uint32_t v) { return __uint_as_float(v & 0xffff0000u); }
__device__ __forceinline__ float round_bf16(float v) { return __uint_as_float(pack_bf16(0.f, v)); }
__device__ __forceinline__ uint32_t sub_bf16x2(uint32_t a, uint32_t b) {
  uint32_t r;
  asm("sub.rn.bf16x2 %0, %1, %2;" : "=r"(r) : "r"(a), "r"(b));
  return r;
}
__device__ __forceinline__ uint32_t add_bf16x2(uint32_t a, uint32_t b) {
  uint32_t r;
  asm("add.rn.bf16x2 %0, %1, %2;" : "=r"(r) : "r"(a), "r"(b));
  return r;
}
__device__ __forceinline__ uint32_t mul_bf16x2(uint32_t a, uint32_t b) {
  uint32_t r;
  asm("mul.rn.bf16x2 %0, %1, %2;" : "=r"(r) : "r"(a), "r"(b));
  return r;
}
__device__ __forceinline__ uint32_t fma_bf16x2(uint32_t a, uint32_t b, uint32_t c) {
  uint32_t r;
  asm("fma.rn.bf16x2 %0, %1, %2, %3;" : "=r"(r) : "r"(a), "r"(b), "r"(c));
  return r;
}
__device__ __forceinline__ float ln_rstd(float var) {
  float sd, r;
  asm("sqrt.approx.ftz.f32 %0, %1;" : "=f"(sd) : "f"(round_bf16(round_bf16(var) + 1e-5f)));
  asm("rcp.approx.ftz.f32 %0, %1;" : "=f"(r) : "f"(round_bf16(sd)));
  return r;
}
__device__ __forceinline__ float tanh_hw(float x) {
  float r;
  asm("tanh.approx.f32 %0, %1;" : "=f"(r) : "f"(x));
  return r;
}
__device__ __forceinline__ unsigned ld_acquire(const unsigned* p) {
  unsigned v;
  asm volatile("ld.acquire.gpu.global.u32 %0, [%1];" : "=r"(v) : "l"(p) : "memory");
  return v;
}
__device__ __forceinline__ void wait_flag(const unsigned* p, unsigned target) {
  uint32_t c = 0;
  while ((int)(ld_acquire(p) - target) < 0) {
    if (++c > SPIN_LIMIT) __trap();
  }
}
__device__ __forceinline__ void red_add(unsigned* p, unsigned v) {
  asm volatile("red.relaxed.gpu.global.add.u32 [%0], %1;" ::"l"(p), "r"(v) : "memory");
}
#define WG_FENCE() asm volatile("wgmma.fence.sync.aligned;" ::: "memory")
#define WG_COMMIT() asm volatile("wgmma.commit_group.sync.aligned;" ::: "memory")
#define WG_WAIT(n) asm volatile("wgmma.wait_group.sync.aligned %0;" ::"n"(n) : "memory")

template <int TB>
__device__ __forceinline__ void wgmma_n16(float* d, const uint32_t* a, uint64_t db, int accum) {
  asm volatile(
      "{\n.reg .pred p;\nsetp.ne.b32 p, %13, 0;\n"
      "wgmma.mma_async.sync.aligned.m64n16k16.f32.bf16.bf16 "
      "{%0,%1,%2,%3,%4,%5,%6,%7}, "
      "{%8,%9,%10,%11}, %12, p, 1, 1, %14;\n}\n"
      : "+f"(d[0]), "+f"(d[1]), "+f"(d[2]), "+f"(d[3]), "+f"(d[4]), "+f"(d[5]), "+f"(d[6]), "+f"(d[7])
      : "r"(a[0]), "r"(a[1]), "r"(a[2]), "r"(a[3]), "l"(db), "r"(accum), "n"(TB));
}
template <int TB>
__device__ __forceinline__ void wgmma_n32(float* d, const uint32_t* a, uint64_t db, int accum) {
  asm volatile(
      "{\n.reg .pred p;\nsetp.ne.b32 p, %21, 0;\n"
      "wgmma.mma_async.sync.aligned.m64n32k16.f32.bf16.bf16 "
      "{%0,%1,%2,%3,%4,%5,%6,%7,%8,%9,%10,%11,%12,%13,%14,%15}, "
      "{%16,%17,%18,%19}, %20, p, 1, 1, %22;\n}\n"
      : "+f"(d[0]), "+f"(d[1]), "+f"(d[2]), "+f"(d[3]), "+f"(d[4]), "+f"(d[5]), "+f"(d[6]), "+f"(d[7]),
        "+f"(d[8]), "+f"(d[9]), "+f"(d[10]), "+f"(d[11]), "+f"(d[12]), "+f"(d[13]), "+f"(d[14]), "+f"(d[15])
      : "r"(a[0]), "r"(a[1]), "r"(a[2]), "r"(a[3]), "l"(db), "r"(accum), "n"(TB));
}
template <int TB>
__device__ __forceinline__ void wgmma_n48(float* d, const uint32_t* a, uint64_t db, int accum) {
  asm volatile(
      "{\n.reg .pred p;\nsetp.ne.b32 p, %29, 0;\n"
      "wgmma.mma_async.sync.aligned.m64n48k16.f32.bf16.bf16 "
      "{%0,%1,%2,%3,%4,%5,%6,%7,%8,%9,%10,%11,%12,%13,%14,%15,%16,%17,%18,%19,%20,%21,%22,%23}, "
      "{%24,%25,%26,%27}, %28, p, 1, 1, %30;\n}\n"
      : "+f"(d[0]), "+f"(d[1]), "+f"(d[2]), "+f"(d[3]), "+f"(d[4]), "+f"(d[5]), "+f"(d[6]), "+f"(d[7]),
        "+f"(d[8]), "+f"(d[9]), "+f"(d[10]), "+f"(d[11]), "+f"(d[12]), "+f"(d[13]), "+f"(d[14]), "+f"(d[15]),
        "+f"(d[16]), "+f"(d[17]), "+f"(d[18]), "+f"(d[19]), "+f"(d[20]), "+f"(d[21]), "+f"(d[22]), "+f"(d[23])
      : "r"(a[0]), "r"(a[1]), "r"(a[2]), "r"(a[3]), "l"(db), "r"(accum), "n"(TB));
}
template <int TB>
__device__ __forceinline__ void wgmma_n64(float* d, const uint32_t* a, uint64_t db, int accum) {
  asm volatile(
      "{\n.reg .pred p;\nsetp.ne.b32 p, %37, 0;\n"
      "wgmma.mma_async.sync.aligned.m64n64k16.f32.bf16.bf16 "
      "{%0,%1,%2,%3,%4,%5,%6,%7,%8,%9,%10,%11,%12,%13,%14,%15,%16,%17,%18,%19,%20,%21,%22,%23,%24,%25,%26,%27,%28,%29,%30,%31}, "
      "{%32,%33,%34,%35}, %36, p, 1, 1, %38;\n}\n"
      : "+f"(d[0]), "+f"(d[1]), "+f"(d[2]), "+f"(d[3]), "+f"(d[4]), "+f"(d[5]), "+f"(d[6]), "+f"(d[7]),
        "+f"(d[8]), "+f"(d[9]), "+f"(d[10]), "+f"(d[11]), "+f"(d[12]), "+f"(d[13]), "+f"(d[14]), "+f"(d[15]),
        "+f"(d[16]), "+f"(d[17]), "+f"(d[18]), "+f"(d[19]), "+f"(d[20]), "+f"(d[21]), "+f"(d[22]), "+f"(d[23]),
        "+f"(d[24]), "+f"(d[25]), "+f"(d[26]), "+f"(d[27]), "+f"(d[28]), "+f"(d[29]), "+f"(d[30]), "+f"(d[31])
      : "r"(a[0]), "r"(a[1]), "r"(a[2]), "r"(a[3]), "l"(db), "r"(accum), "n"(TB));
}
template <int TB>
__device__ __forceinline__ void wgmma_n80(float* d, const uint32_t* a, uint64_t db, int accum) {
  asm volatile(
      "{\n.reg .pred p;\nsetp.ne.b32 p, %45, 0;\n"
      "wgmma.mma_async.sync.aligned.m64n80k16.f32.bf16.bf16 "
      "{%0,%1,%2,%3,%4,%5,%6,%7,%8,%9,%10,%11,%12,%13,%14,%15,%16,%17,%18,%19,%20,%21,%22,%23,%24,%25,%26,%27,%28,%29,%30,%31,%32,%33,%34,%35,%36,%37,%38,%39}, "
      "{%40,%41,%42,%43}, %44, p, 1, 1, %46;\n}\n"
      : "+f"(d[0]), "+f"(d[1]), "+f"(d[2]), "+f"(d[3]), "+f"(d[4]), "+f"(d[5]), "+f"(d[6]), "+f"(d[7]),
        "+f"(d[8]), "+f"(d[9]), "+f"(d[10]), "+f"(d[11]), "+f"(d[12]), "+f"(d[13]), "+f"(d[14]), "+f"(d[15]),
        "+f"(d[16]), "+f"(d[17]), "+f"(d[18]), "+f"(d[19]), "+f"(d[20]), "+f"(d[21]), "+f"(d[22]), "+f"(d[23]),
        "+f"(d[24]), "+f"(d[25]), "+f"(d[26]), "+f"(d[27]), "+f"(d[28]), "+f"(d[29]), "+f"(d[30]), "+f"(d[31]),
        "+f"(d[32]), "+f"(d[33]), "+f"(d[34]), "+f"(d[35]), "+f"(d[36]), "+f"(d[37]), "+f"(d[38]), "+f"(d[39])
      : "r"(a[0]), "r"(a[1]), "r"(a[2]), "r"(a[3]), "l"(db), "r"(accum), "n"(TB));
}
template <int TB>
__device__ __forceinline__ void wgmma_n96(float* d, const uint32_t* a, uint64_t db, int accum) {
  asm volatile(
      "{\n.reg .pred p;\nsetp.ne.b32 p, %53, 0;\n"
      "wgmma.mma_async.sync.aligned.m64n96k16.f32.bf16.bf16 "
      "{%0,%1,%2,%3,%4,%5,%6,%7,%8,%9,%10,%11,%12,%13,%14,%15,%16,%17,%18,%19,%20,%21,%22,%23,%24,%25,%26,%27,%28,%29,%30,%31,%32,%33,%34,%35,%36,%37,%38,%39,%40,%41,%42,%43,%44,%45,%46,%47}, "
      "{%48,%49,%50,%51}, %52, p, 1, 1, %54;\n}\n"
      : "+f"(d[0]), "+f"(d[1]), "+f"(d[2]), "+f"(d[3]), "+f"(d[4]), "+f"(d[5]), "+f"(d[6]), "+f"(d[7]),
        "+f"(d[8]), "+f"(d[9]), "+f"(d[10]), "+f"(d[11]), "+f"(d[12]), "+f"(d[13]), "+f"(d[14]), "+f"(d[15]),
        "+f"(d[16]), "+f"(d[17]), "+f"(d[18]), "+f"(d[19]), "+f"(d[20]), "+f"(d[21]), "+f"(d[22]), "+f"(d[23]),
        "+f"(d[24]), "+f"(d[25]), "+f"(d[26]), "+f"(d[27]), "+f"(d[28]), "+f"(d[29]), "+f"(d[30]), "+f"(d[31]),
        "+f"(d[32]), "+f"(d[33]), "+f"(d[34]), "+f"(d[35]), "+f"(d[36]), "+f"(d[37]), "+f"(d[38]), "+f"(d[39]),
        "+f"(d[40]), "+f"(d[41]), "+f"(d[42]), "+f"(d[43]), "+f"(d[44]), "+f"(d[45]), "+f"(d[46]), "+f"(d[47])
      : "r"(a[0]), "r"(a[1]), "r"(a[2]), "r"(a[3]), "l"(db), "r"(accum), "n"(TB));
}
template <int TB>
__device__ __forceinline__ void wgmma_n112(float* d, const uint32_t* a, uint64_t db, int accum) {
  asm volatile(
      "{\n.reg .pred p;\nsetp.ne.b32 p, %61, 0;\n"
      "wgmma.mma_async.sync.aligned.m64n112k16.f32.bf16.bf16 "
      "{%0,%1,%2,%3,%4,%5,%6,%7,%8,%9,%10,%11,%12,%13,%14,%15,%16,%17,%18,%19,%20,%21,%22,%23,%24,%25,%26,%27,%28,%29,%30,%31,%32,%33,%34,%35,%36,%37,%38,%39,%40,%41,%42,%43,%44,%45,%46,%47,%48,%49,%50,%51,%52,%53,%54,%55}, "
      "{%56,%57,%58,%59}, %60, p, 1, 1, %62;\n}\n"
      : "+f"(d[0]), "+f"(d[1]), "+f"(d[2]), "+f"(d[3]), "+f"(d[4]), "+f"(d[5]), "+f"(d[6]), "+f"(d[7]),
        "+f"(d[8]), "+f"(d[9]), "+f"(d[10]), "+f"(d[11]), "+f"(d[12]), "+f"(d[13]), "+f"(d[14]), "+f"(d[15]),
        "+f"(d[16]), "+f"(d[17]), "+f"(d[18]), "+f"(d[19]), "+f"(d[20]), "+f"(d[21]), "+f"(d[22]), "+f"(d[23]),
        "+f"(d[24]), "+f"(d[25]), "+f"(d[26]), "+f"(d[27]), "+f"(d[28]), "+f"(d[29]), "+f"(d[30]), "+f"(d[31]),
        "+f"(d[32]), "+f"(d[33]), "+f"(d[34]), "+f"(d[35]), "+f"(d[36]), "+f"(d[37]), "+f"(d[38]), "+f"(d[39]),
        "+f"(d[40]), "+f"(d[41]), "+f"(d[42]), "+f"(d[43]), "+f"(d[44]), "+f"(d[45]), "+f"(d[46]), "+f"(d[47]),
        "+f"(d[48]), "+f"(d[49]), "+f"(d[50]), "+f"(d[51]), "+f"(d[52]), "+f"(d[53]), "+f"(d[54]), "+f"(d[55])
      : "r"(a[0]), "r"(a[1]), "r"(a[2]), "r"(a[3]), "l"(db), "r"(accum), "n"(TB));
}
template <int TB>
__device__ __forceinline__ void wgmma_n128(float* d, const uint32_t* a, uint64_t db, int accum) {
  asm volatile(
      "{\n.reg .pred p;\nsetp.ne.b32 p, %69, 0;\n"
      "wgmma.mma_async.sync.aligned.m64n128k16.f32.bf16.bf16 "
      "{%0,%1,%2,%3,%4,%5,%6,%7,%8,%9,%10,%11,%12,%13,%14,%15,%16,%17,%18,%19,%20,%21,%22,%23,%24,%25,%26,%27,%28,%29,%30,%31,%32,%33,%34,%35,%36,%37,%38,%39,%40,%41,%42,%43,%44,%45,%46,%47,%48,%49,%50,%51,%52,%53,%54,%55,%56,%57,%58,%59,%60,%61,%62,%63}, "
      "{%64,%65,%66,%67}, %68, p, 1, 1, %70;\n}\n"
      : "+f"(d[0]), "+f"(d[1]), "+f"(d[2]), "+f"(d[3]), "+f"(d[4]), "+f"(d[5]), "+f"(d[6]), "+f"(d[7]),
        "+f"(d[8]), "+f"(d[9]), "+f"(d[10]), "+f"(d[11]), "+f"(d[12]), "+f"(d[13]), "+f"(d[14]), "+f"(d[15]),
        "+f"(d[16]), "+f"(d[17]), "+f"(d[18]), "+f"(d[19]), "+f"(d[20]), "+f"(d[21]), "+f"(d[22]), "+f"(d[23]),
        "+f"(d[24]), "+f"(d[25]), "+f"(d[26]), "+f"(d[27]), "+f"(d[28]), "+f"(d[29]), "+f"(d[30]), "+f"(d[31]),
        "+f"(d[32]), "+f"(d[33]), "+f"(d[34]), "+f"(d[35]), "+f"(d[36]), "+f"(d[37]), "+f"(d[38]), "+f"(d[39]),
        "+f"(d[40]), "+f"(d[41]), "+f"(d[42]), "+f"(d[43]), "+f"(d[44]), "+f"(d[45]), "+f"(d[46]), "+f"(d[47]),
        "+f"(d[48]), "+f"(d[49]), "+f"(d[50]), "+f"(d[51]), "+f"(d[52]), "+f"(d[53]), "+f"(d[54]), "+f"(d[55]),
        "+f"(d[56]), "+f"(d[57]), "+f"(d[58]), "+f"(d[59]), "+f"(d[60]), "+f"(d[61]), "+f"(d[62]), "+f"(d[63])
      : "r"(a[0]), "r"(a[1]), "r"(a[2]), "r"(a[3]), "l"(db), "r"(accum), "n"(TB));
}
template <int N, int TB>
__device__ __forceinline__ void wgmma_rs(float* d, const uint32_t* a, uint64_t db, int accum) {
  if constexpr (N == 16) wgmma_n16<TB>(d, a, db, accum);
  if constexpr (N == 32) wgmma_n32<TB>(d, a, db, accum);
  if constexpr (N == 48) wgmma_n48<TB>(d, a, db, accum);
  if constexpr (N == 64) wgmma_n64<TB>(d, a, db, accum);
  if constexpr (N == 80) wgmma_n80<TB>(d, a, db, accum);
  if constexpr (N == 96) wgmma_n96<TB>(d, a, db, accum);
  if constexpr (N == 112) wgmma_n112<TB>(d, a, db, accum);
  if constexpr (N == 128) wgmma_n128<TB>(d, a, db, accum);
}

struct SsmParams {
  const __nv_bfloat16 *a_re, *a_im, *b_re, *b_im, *c_re, *c_im, *log_dt, *x, *dskip;
  Scratch* g;
};
struct C2 {
  float r, i;
};
__device__ __forceinline__ C2 cmul(C2 a, C2 b) { return {fmaf(a.r, b.r, -a.i * b.i), fmaf(a.r, b.i, a.i * b.r)}; }
__device__ __forceinline__ C2 cmulc(C2 a, C2 b) { return {fmaf(a.r, b.r, a.i * b.i), fmaf(a.i, b.r, -a.r * b.i)}; }
__device__ __forceinline__ C2 cexp_pow(float a2, float rev, float l) {
  float m, t = rev * l, sn, cs;
  asm("ex2.approx.ftz.f32 %0, %1;" : "=f"(m) : "f"(a2 * l));
  t = (t - rintf(t)) * 6.283185307179586f;
  asm("sin.approx.ftz.f32 %0, %1;" : "=f"(sn) : "f"(t));
  asm("cos.approx.ftz.f32 %0, %1;" : "=f"(cs) : "f"(t));
  return {m * cs, m * sn};
}
__device__ __forceinline__ void store8(uint32_t addr, const C2* v) {
  uint32_t re[4], im[4];
#pragma unroll
  for (int i = 0; i < 4; i++) {
    re[i] = pack_bf16(v[2 * i].r, v[2 * i + 1].r);
    im[i] = pack_bf16(v[2 * i].i, v[2 * i + 1].i);
  }
  sts128(addr, re);
  sts128(addr + WS_WARP / 2, im);
}
struct ModeIn {
  uint32_t ar, ai, br, bi, cr, ci, ldt;
};
__device__ __forceinline__ uint32_t ldg16(const __nv_bfloat16* p) {
  uint32_t r;
  asm volatile("ld.global.nc.u16 %0, [%1];" : "=r"(r) : "l"(p));
  return r;
}
__device__ __forceinline__ uint32_t ldg32(const __nv_bfloat16* p) {
  uint32_t r;
  asm volatile("ld.global.nc.u32 %0, [%1];" : "=r"(r) : "l"(p));
  return r;
}
__device__ __forceinline__ ModeIn load_modes(const SsmParams& p, uint32_t d, uint32_t pair) {
  const uint32_t i = d * NMODE + 2 * pair;
  return {ldg32(p.a_re + i), ldg32(p.a_im + i), ldg32(p.b_re + i), ldg32(p.b_im + i),
          ldg32(p.c_re + i), ldg32(p.c_im + i), ldg16(p.log_dt + d)};
}

__device__ __forceinline__ void kgen_modes(uint32_t my, const ModeIn in, uint32_t sel, float (&acc)[6][4]) {
  const int lane = fresh_tid() & 31;
  const uint32_t row = my + lane * 112;
  auto pick = [&](uint32_t v) { return __uint_as_float(__byte_perm(v, 0, sel)); };
  const float dt = round_bf16(__expf(bf_lo(in.ldt)));
  const float a2 = dt * pick(in.ar) * 1.4426950408889634f, rev = dt * pick(in.ai) * 0.15915494309189535f;
  const C2 e1 = cexp_pow(a2, rev, 1.f), e8 = cexp_pow(a2, rev, 8.f), e256 = cexp_pow(a2, rev, 256.f);
  {
    C2 y[8];
    y[0] = {1.f, 0.f};
    y[1] = e8;
    y[2] = cmul(e8, e8);
    y[3] = cmul(y[2], e8);
    y[4] = cmul(y[2], y[2]);
    y[5] = cmul(y[4], y[1]);
    y[6] = cmul(y[4], y[2]);
    y[7] = cmul(y[4], y[3]);
    const C2 e64 = cmul(y[4], y[4]);
    store8(row, y);
#pragma unroll
    for (int c = 1; c < 4; c++) {
#pragma unroll
      for (int i = 0; i < 8; i++) y[i] = (c == 1 && i == 0) ? e64 : cmul(y[i], e64);
      store8(row + 16 * c, y);
    }
  }
  {
    C2 x[8], z[8];
    x[0] = cmulc({pick(in.cr), -pick(in.ci)}, {dt * pick(in.br), dt * pick(in.bi)});
    x[1] = cmulc(x[0], e1);
    const C2 e2 = cmul(e1, e1);
#pragma unroll
    for (int i = 2; i < 8; i++) x[i] = cmulc(x[i - 2], e2);
    store8(row + 64, x);
#pragma unroll
    for (int i = 0; i < 4; i++) z[i] = cmulc(x[2 * i], e256);
    z[4] = cmulc(z[0], e256);
    z[5] = cmulc(z[2], e256);
    z[6] = cmulc(z[4], e256);
    z[7] = cmulc(z[5], e256);
    store8(row + 80, z);
    const C2 e512 = cmul(e256, e256);
    x[0] = cmulc(z[4], e512);
    x[1] = cmulc(z[6], e512);
    x[2] = cmulc(x[0], e512);
    x[3] = cmulc(x[1], e512);
    x[4] = cmulc(x[2], e512);
    x[5] = x[6] = x[7] = {0.f, 0.f};
    store8(row + 96, x);
  }
  __syncwarp();
  const uint32_t aa = my + (lane >> 4) * (WS_WARP / 2) + (lane & 7) * 112 + ((lane >> 3) & 1) * 16;
  const uint32_t ba = my + ((lane >> 3) & 1) * (WS_WARP / 2) + (lane & 7) * 112 + (lane >> 4) * 16 + 64;
#pragma unroll
  for (int ks = 0; ks < 4; ks++) {
    uint32_t a[2][4], b[6];
    ldsm4t(a[0], aa + ks * 896);
    ldsm4t(a[1], aa + ks * 896 + 32);
    ldsm4t(b, ba + ks * 896);
    ldsm2t(b + 4, ba + ks * 896 + 32);
#pragma unroll
    for (int nt = 0; nt < 3; nt++)
#pragma unroll
      for (int mt = 0; mt < 2; mt++) mma_bf16(acc[nt * 2 + mt], a[mt][0], a[mt][1], a[mt][2], a[mt][3], &b[2 * nt]);
  }
  __syncwarp();
}

__device__ __forceinline__ void stats_load(Scratch* g, uint32_t (&st)[12]) {
  const uint4* sp = &g->stats[fresh_tid()];
#pragma unroll
  for (int e = 0; e < 3; e++) {
    uint32_t* v = &st[4 * e];
    asm volatile("ld.relaxed.gpu.global.v4.b32 {%0,%1,%2,%3}, [%4];"
                 : "=r"(v[0]), "=r"(v[1]), "=r"(v[2]), "=r"(v[3]) : "l"(sp + 256 * e) : "memory");
  }
}
__device__ __forceinline__ void kgen_finish(uint32_t sb, Scratch* g, int wg, const float (&acc)[6][4], uint32_t (&st)[12]) {
  const int t = fresh_tid() & 127;
  const uint32_t ws = sb + OFF_WS + wg * WS_BYTES;
#pragma unroll
  for (int i = 0; i < 6; i++)
    sts128(ws + (t >> 5) * WS_WARP + i * 512 + (t & 31) * 16, reinterpret_cast<const uint32_t*>(acc[i]));
  if (t < 2) sts32(ws + WS_KC - 4 + t * KC_PITCH, 0);
  STAMPC(threadIdx.x == 0, 15);
  wg_bar(wg);
  STAMPC(threadIdx.x == 0, 16);
  {
    uint32_t v[3][4][2], pk[3][2];
#pragma unroll
    for (int k = 0; k < 3; k++)
#pragma unroll
      for (int src = 0; src < 4; src++) lds64(v[k][src], ws + src * WS_WARP + k * 1024 + t * 8);
    const float f = wg == 2 ? 1.f : 0.f;
#pragma unroll
    for (int k = 0; k < 3; k++) {
      const float b0 = __uint_as_float(v[k][2][0]) + __uint_as_float(v[k][3][0]);
      const float b1 = __uint_as_float(v[k][2][1]) + __uint_as_float(v[k][3][1]);
      const float a0 = __uint_as_float(v[k][0][0]) + __uint_as_float(v[k][1][0]);
      const float a1 = __uint_as_float(v[k][0][1]) + __uint_as_float(v[k][1][1]);
      pk[k][0] = f != 0.f ? pack_bf16(a0 + b0, a1 + b1) : pack_bf16(a0, a1);
      pk[k][1] = pack_bf16(b0, b1);
    }
    const int q = (t >> 1) & 3, j = (t >> 6) * 16 + ((t >> 3) & 7) + (t & 1) * 8;
#pragma unroll
    for (int ch = 0; ch < 2; ch++) {
      const uint32_t kc = ws + WS_KC + ch * KC_PITCH;
      sts32(kc + 2 * (8 * j + 2 * q), pk[0][ch]);
      sts32(kc + 2 * (q < 2 ? 256 + 4 * j + 2 * q : 256 + 64 * q + 2 * j), pk[1][ch]);
      if (q < 2 || (q == 2 && j == 0)) sts16(kc + 2 * (512 + 64 * q + j), pk[2][ch]);
      if (q < 2) sts16(kc + 2 * (544 + 64 * q + j), pk[2][ch] >> 16);
    }
  }
  wg_bar(wg);
  STAMPC(threadIdx.x == 0, 17);
  if (wg < 2) stats_load(g, st);
  uint32_t v[2][9];
  const bool dense = t < 64;
#pragma unroll
  for (int ch = 0; ch < 2; ch++) {
    const uint32_t kc = ws + WS_KC + ch * KC_PITCH, k0 = kc + (dense ? 8 * t : 256 + 4 * t);
    v[ch][0] = lds32(k0);
    v[ch][1] = lds32(k0 + 4);
    v[ch][2] = lds16(k0 - (t <= 64 ? 2 : 0));
    v[ch][3] = lds16(kc + 2 * (384 + t));
    v[ch][4] = lds16(kc + 2 * (385 + t));
#pragma unroll
    for (int k = 0; k < 2; k++) {
      v[ch][5 + 2 * k] = lds16(kc + 2 * (512 + 64 * k + (t >> 1)));
      v[ch][6 + 2 * k] = lds16(kc + 2 * (512 + 64 * k + ((t + 1) >> 1)));
    }
  }
  const uint32_t s1 = dense ? 0x1032 : 0x1010, s2 = dense ? 0x7610 : 0x5476, s3 = dense ? 0x1032 : 0x7610;
#pragma unroll
  for (int ch = 0; ch < 2; ch++) {
    if (ch == 1 && wg == 2) break;
    const uint32_t pkb = sb + OFF_PK + (2 * wg + ch) * PK_PITCH + 32 + t * 16;
    uint32_t o[4];
    o[0] = __byte_perm(v[ch][0], v[ch][2], 0x5410);
    o[1] = __byte_perm(v[ch][0], 0, s1);
    o[2] = __byte_perm(v[ch][1], v[ch][0], s2);
    o[3] = __byte_perm(v[ch][1], v[ch][0], s3);
    sts128(pkb, o);
    uint32_t vm = (t & 1) ? v[ch][4] : v[ch][3];
    o[0] = o[1] = __byte_perm(v[ch][3], 0, 0x1010);
    o[2] = __byte_perm(vm, v[ch][3], 0x5410);
    o[3] = __byte_perm(v[ch][4], vm, 0x5410);
    sts128(pkb + 2048, o);
#pragma unroll
    for (int k = 0; k < 2; k++) {
      const uint32_t v0 = v[ch][5 + 2 * k], v1 = v[ch][6 + 2 * k];
      vm = (t & 2) ? v1 : v0;
      o[0] = __byte_perm(vm, v0, 0x5410);
      o[1] = __byte_perm(v1, vm, 0x5410);
      o[2] = o[3] = __byte_perm(v1, 0, 0x1010);
      sts128(pkb + 4096 + 2048 * k, o);
    }
  }
}

__device__ __forceinline__ uint32_t copy_reg(uint32_t v) {
  uint32_t r;
  asm volatile("mov.b32 %0, %1;" : "=r"(r) : "r"(v));
  return r;
}
struct ConvCtx {
  uint32_t pa, pw, pr, ub, xb, dsk;
  uint64_t db;
  uint4* hrow;
  int wg, t;
  uint32_t sig;
};
__device__ __forceinline__ void conv_emit(const ConvCtx& c, int k) {
  uint32_t v[6][4], h[4];
  wg_bar(c.wg);
#pragma unroll
  for (int src = 0; src < 4; src++) lds128(v[src], k == 0 && c.t < src ? c.ub - 64 : c.pr + src * 4080 + 2048 * k);
  lds128(v[4], c.ub + 2048 * k);
  lds128(v[5], c.xb + 2048 * k);
#pragma unroll
  for (int e = 0; e < 4; e++) {
    const uint32_t y = add_bf16x2(add_bf16x2(v[0][e], v[1][e]), add_bf16x2(v[2][e], v[3][e]));
    h[e] = add_bf16x2(v[5][e], add_bf16x2(y, mul_bf16x2(v[4][e], c.dsk)));
  }
  c.hrow[128 * k] = make_uint4(h[0], h[1], h[2], h[3]);
}
__device__ __forceinline__ void conv_spill(const ConvCtx& c, const float* acc, int b) {
  uint32_t p[4];
#pragma unroll
  for (int e = 0; e < 4; e++) p[e] = pack_bf16(acc[2 * e], acc[2 * e + 1]);
  asm volatile("stmatrix.sync.aligned.m8n8.x4.trans.shared.b16 [%0], {%1,%2,%3,%4};"
               ::"r"(c.pw + b * 512), "r"(p[0]), "r"(p[1]), "r"(p[2]), "r"(p[3]) : "memory");
}
template <int B>
__device__ __forceinline__ void conv_batches(const ConvCtx& c, float (&acc)[64], uint32_t (&a)[2][4][4]) {
  constexpr int N = (B + 1) & 1;
  WG_FENCE();
#pragma unroll
  for (int k = 0; k < 4; k++) wgmma_rs<128 - 16 * B, 0>(acc + 8 * B, a[B & 1][k], c.db - 16 * (k >> 1) - 4 * (k & 1), B + k);
  WG_COMMIT();
  if constexpr (B < 7) {
#pragma unroll
    for (int k = 0; k < 4; k++) {
      const uint32_t o = c.pa + 1024 * (B + 1) + 512 * (k >> 1) + 128 * (k & 1);
      a[N][k][0] = lds32(o);
      a[N][k][1] = lds32(o + 256);
    }
  }
  if constexpr (B == 0) wg_bar(c.wg);
  if constexpr (B > 0) conv_spill(c, acc + 8 * (B - 1), B - 1);
  if constexpr (B == 4) {
    conv_emit(c, 0);
    __syncwarp();
    if (c.sig) mbar_arrive(c.sig);
  }
  WG_WAIT(0);
#pragma unroll
  for (int i = 8 * B; i < 64; i++) asm volatile("mov.b32 %0, %1;" : "=f"(acc[i]) : "f"(acc[i]));
  if constexpr (B < 7) {
#pragma unroll
    for (int k = 0; k < 4; k++) {
      a[N][k][2] = copy_reg(k < 2 ? a[B & 1][k + 2][1] : a[N][k - 2][1]);
      a[N][k][3] = copy_reg(a[N][k][0]);
    }
    conv_batches<B + 1>(c, acc, a);
  }
}

__device__ __forceinline__ void conv_task(uint32_t sb, Scratch* g, int wg, int w, int local, int d, bool last) {
  const int t = fresh_tid() & 127, lane = t & 31;
  const uint32_t ub = sb + OFF_U + local * U_PITCH + U_PAD, part = sb + OFF_PART + wg * SLOT;
  ConvCtx c;
  c.pa = sb + OFF_PK + local * PK_PITCH + 32 + 4 * (8 * w + (lane >> 2) - 2 * (lane & 3));
  c.pw = part + w * 4096 + lane * 16;
  c.pr = part + 16 * t;
  c.ub = ub + 16 * t;
  c.xb = sb + OFF_X + local * X_PITCH + 16 * t;
  c.dsk = lds32(sb + OFF_MISC + 120 + 4 * local);
  c.db = (uint64_t)((ub & 0x3FFFF) >> 4) | ((uint64_t)(128 >> 4) << 16) | ((uint64_t)(256 >> 4) << 32);
  c.hrow = reinterpret_cast<uint4*>(g->hT + d * L) + t;
  c.wg = wg;
  c.t = t;
  c.sig = last && lane == 0 ? sb + B_CV : 0;
  float acc[64];
  uint32_t a[2][4][4];
#pragma unroll
  for (int k = 0; k < 4; k++) {
    const uint32_t o = c.pa + 512 * (k >> 1) + 128 * (k & 1);
    a[0][k][0] = lds32(o);
    a[0][k][1] = lds32(o + 256);
    a[0][k][2] = copy_reg(k < 2 ? 0 : a[0][k & 1][1]);
    a[0][k][3] = copy_reg(a[0][k][0]);
  }
  conv_batches<0>(c, acc, a);
  STAMP(32 + wg + 3 * last);
  conv_spill(c, acc + 56, 7);
  conv_emit(c, 1);
}

__device__ __forceinline__ void mma_k8(float* c, uint32_t a0, uint32_t a1, uint32_t b) {
  asm volatile("mma.sync.aligned.m16n8k8.row.col.f32.bf16.bf16.f32 {%0,%1,%2,%3}, {%4,%5}, {%6}, {%0,%1,%2,%3};"
               : "+f"(c[0]), "+f"(c[1]), "+f"(c[2]), "+f"(c[3]) : "r"(a0), "r"(a1), "r"(b));
}

__device__ __forceinline__ void ln1_stats(uint32_t sb, Scratch* g, int c, const uint4 (&xv)[9]) {
  const int t = fresh_tid() & 127, lane = t & 31;
  float st[5][4];
#pragma unroll
  for (int i = 0; i < 5; i++) st[i][0] = st[i][1] = st[i][2] = st[i][3] = 0.f;
  const uint32_t ones[2] = {0x3f803f80u, 0x3f803f80u};
#pragma unroll
  for (int i = 0; i < 9; i++) {
    mma_bf16(st[0], xv[i].x, xv[i].y, xv[i].z, xv[i].w, ones);
    mma_k8(st[1], xv[i].x, xv[i].y, xv[i].x);
    mma_k8(st[2], xv[i].x, xv[i].y, xv[i].y);
    mma_k8(st[3], xv[i].z, xv[i].w, xv[i].z);
    mma_k8(st[4], xv[i].z, xv[i].w, xv[i].w);
  }
  float s = st[0][0] + st[0][2];
  float q = (lane & 4) ? (st[1][1] + st[3][1]) + (st[2][3] + st[4][3]) : (st[1][0] + st[3][0]) + (st[2][2] + st[4][2]);
  s += __shfl_xor_sync(~0u, s, 4);
  q += __shfl_xor_sync(~0u, q, 4);
  q = __shfl_sync(~0u, q, (lane & 24) + (lane >> 3));
  const float m = s * (1.f / D), r = ln_rstd(fmaxf(q * (1.f / D) - m * m, 0.f));
  const int sub = t & 7;
  const uint32_t b = pack_bf16(sub == 0 ? m : sub == 1 ? r : r - round_bf16(r), 0.f);
  if (sub < 3) sts16(sb + OFF_MISC + sub * 32 + (t >> 3) * 2, b ? b : 0x8000u);
  wg_bar(2);
  if (t < 6) {
    uint32_t v[4];
    lds128(v, sb + OFF_MISC + t * 16);
    asm volatile("st.relaxed.gpu.global.v4.b32 [%0], {%1,%2,%3,%4};" ::"l"(&g->stats[(t >> 1) * 256 + 2 * c + (t & 1)]),
                 "r"(v[0]), "r"(v[1]), "r"(v[2]), "r"(v[3]) : "memory");
  }
}

__device__ __forceinline__ void x_transpose(uint32_t sb, int c, int w) {
  const int lane = fresh_tid() & 31, rank = c & 1;
  uint32_t dx[2];
#pragma unroll
  for (int hf = 0; hf < 2; hf++) {
    const int rel = 8 * hf + (lane >> 2) - ((c >> 1) & 7), loc = rel > 4 ? rel - 5 : rel;
    dx[hf] = (rel > 4) == rank ? OFF_X + loc * X_PITCH + 2048 * rank : OFF_STG + loc * STG_PITCH;
    dx[hf] = rel >= 0 && rel < 9 ? sb + dx[hf] + 16 * (lane & 3) + 64 * w : 0;
  }
#pragma unroll 1
  for (int half = 0; half < 2; half++) {
    mbar_wait(sb + B_G + 8 * half, 0);
    STAMPC(w == 0 && lane == 0, 56 + half);
    uint32_t x[8][4];
#pragma unroll
    for (int i = 0; i < 8; i++)
      ldsm4t(x[i], sb + OFF_G + (16 * half + 4 * (i >> 1) + w) * 1024 + lane * 32 + (((i ^ (lane >> 2)) & 1) << 4));
#pragma unroll
    for (int i = 0; i < 8; i++)
      if (dx[i & 1]) sts128(dx[i & 1] + 1024 * half + 256 * (i >> 1), x[i]);
  }
  asm volatile("fence.proxy.async.shared::cta;" ::: "memory");
  wg_bar(2);
  if (elect_one()) {
    const uint32_t pb = mapa(sb, rank ^ 1), dst = pb + OFF_X + 2048 * rank;
    bulk_peer(dst + w * X_PITCH, sb + OFF_STG + w * STG_PITCH, 2048, pb + B_UX);
    if (w == 0) bulk_peer(dst + 4 * X_PITCH, sb + OFF_STG + 4 * STG_PITCH, 2048, pb + B_UX);
    if (w == 1) mbar_arrive(sb + B_UX);
  }
  __syncwarp();
}

__device__ __forceinline__ void ln1_apply(uint32_t sb, Scratch* g, uint32_t (&st)[12]) {
  const int t = fresh_tid();
  for (uint32_t spins = 0;; spins++) {
    uint32_t mn = ~0u;
#pragma unroll
    for (int e = 0; e < 12; e++) mn = min(mn, st[e]);
    if (__all_sync(~0u, mn != 0)) break;
    if (spins > SPIN_LIMIT) __trap();
    stats_load(g, st);
  }
  STAMPC(t == 0, 60);
  mbar_wait(sb + B_UX, 0);
  STAMPC(t == 0, 61);
  uint32_t x[5][4];
#pragma unroll
  for (int ch = 0; ch < 5; ch++) lds128(x[ch], sb + OFF_X + ch * X_PITCH + 16 * t);
#pragma unroll
  for (int ch = 0; ch < 5; ch++) {
#pragma unroll
    for (int e = 0; e < 4; e++) {
      const uint32_t dv = sub_bf16x2(x[ch][e], st[e]);
      x[ch][e] = fma_bf16x2(dv, st[4 + e], mul_bf16x2(dv, st[8 + e]));
    }
    sts128(sb + OFF_U + ch * U_PITCH + U_PAD + 16 * t, x[ch]);
  }
}

struct Ring {
  uint32_t slot, phase;
  __device__ __forceinline__ uint32_t off() const { return slot * SLOT; }
  __device__ __forceinline__ void next() {
    if (++slot == NS) { slot = 0; phase ^= 1; }
  }
};

__device__ __forceinline__ uint64_t bdesc(uint32_t addr) {
  return (uint64_t)((addr & 0x3FFFF) >> 4) | ((uint64_t)(BOX >> 4) << 16) | ((uint64_t)(1024 >> 4) << 32) | (1ull << 62);
}
__device__ __forceinline__ void release_slot(uint32_t sb, uint32_t slot, int lane) {
  if (lane == 0) mbar_arrive(sb + B_EMPTY + 8 * slot);
}
__device__ __forceinline__ void stage_partial(const float* acc, uint32_t addr) {
#pragma unroll
  for (int j = 0; j < 4; j++) {
    uint32_t p[4];
#pragma unroll
    for (int i = 0; i < 4; i++) p[i] = pack_bf16(acc[8 * j + 2 * i], acc[8 * j + 2 * i + 1]);
    sts128(addr + j * 512, p);
  }
}
__device__ __forceinline__ void stage_done(uint32_t bar, int lane) {
  asm volatile("fence.proxy.async.shared::cta;" ::: "memory");
  __syncwarp();
  if (lane == 0) mbar_arrive(bar);
}
__device__ __forceinline__ void lds128_if(uint32_t* r, uint32_t a, bool on) {
  asm volatile("{\n.reg .pred p;\nsetp.ne.u32 p, %5, 0;\n@p ld.shared.v4.b32 {%0,%1,%2,%3}, [%4];\n}\n"
               : "+r"(r[0]), "+r"(r[1]), "+r"(r[2]), "+r"(r[3]) : "r"(a), "r"((uint32_t)on) : "memory");
}
__device__ __forceinline__ void stage_sum(const float* acc, const uint32_t* add, uint32_t addr) {
#pragma unroll
  for (int j = 0; j < 4; j++) {
    uint32_t p[4];
#pragma unroll
    for (int i = 0; i < 4; i++) p[i] = add_bf16x2(add[4 * j + i], pack_bf16(acc[8 * j + 2 * i], acc[8 * j + 2 * i + 1]));
    sts128(addr + j * 512, p);
  }
}
__device__ __forceinline__ void lag_sync(int wg) {
  if (wg == 1) asm volatile("bar.sync 4, 256;" ::: "memory");
}
__device__ __forceinline__ void lag_arrive(int wg) {
  if (wg == 0) asm volatile("bar.arrive 4, 256;" ::: "memory");
}

__device__ __forceinline__ void add_packed(uint32_t* d, uint32_t a0, uint32_t a1) {
#pragma unroll
  for (int j = 0; j < 4; j++) {
    uint32_t v[4];
    lds128(d + 4 * j, a0 + j * 512);
    lds128(v, a1 + j * 512);
#pragma unroll
    for (int i = 0; i < 4; i++) d[4 * j + i] = add_bf16x2(d[4 * j + i], v[i]);
  }
}

template <int T, typename Fn>
__device__ __forceinline__ void step64(float (&acc)[32], const uint32_t (&A)[144], uint32_t sb, uint64_t desc0, Ring& ring,
                                       int wg, int lane, Fn&& side) {
  uint32_t prev = 0;
  ring.slot = __shfl_sync(~0u, ring.slot, 0);
#pragma unroll
  for (int st = 0; st < 5; st++) {
    mbar_wait(sb + B_FULL + 8 * ring.slot, ring.phase);
    const uint64_t db = desc0 + (ring.off() >> 4);
    if (st == 5 - LAG3) lag_sync(wg);
    WG_FENCE();
#pragma unroll
    for (int k = 0; k < (st < 4 ? 8 : 4); k++) wgmma_rs<64, 1>(acc, &A[(st * 8 + k) * 4], db + k * 128, st + k);
    WG_COMMIT();
    if (st == 4) lag_arrive(wg);
    if (st > 0 && T * 5 + st - 1 < 15 - NS) {
      WG_WAIT(1);
      release_slot(sb, prev, lane);
    }
    prev = ring.slot;
    ring.next();
    side(st);
  }
  WG_WAIT(0);
  if (T * 5 + 4 < 15 - NS) release_slot(sb, prev, lane);
}

__device__ __forceinline__ void ffn_consumer(uint32_t sb, Scratch* g, int warp, int r, int s, __nv_bfloat16* __restrict__ out) {
  const int tid = fresh_tid(), wg = warp >> 2, w = warp & 3, lane = tid & 31;
  const uint32_t stash = OFF_STASH + wg * STASH_STRIDE;
  const uint32_t priv = sb + stash + w * 2048 + lane * 16;
  uint32_t A[144];
  float rs0, rs1;
  const uint32_t tr_off = ((lane >> 4) * 8 + (lane & 7)) * 128 + (((2 * w + ((lane >> 3) & 1)) ^ (lane & 7)) << 4);
  {
    float st[4][4];
#pragma unroll
    for (int i = 0; i < 4; i++) st[i][0] = st[i][1] = st[i][2] = st[i][3] = 0.f;
    const uint32_t ones[2] = {0x3f803f80u, 0x3f803f80u};
    const bool up = s & 1;
#pragma unroll
    for (int kb = 0; kb < 9; kb++) {
      if (kb == 0 || (kb & 1)) mbar_wait(sb + B_H + 8 * (wg * 5 + (kb + 1) / 2), 0);
      const uint32_t box = sb + (kb ? stash + (kb - 1) * BOX : (NS - 1) * SLOT + wg * BOX) + tr_off;
#pragma unroll
      for (int k = 0; k < 4; k++) {
        uint32_t* a = &A[(kb * 4 + k) * 4];
        ldsm4t(a, box + k * 2048);
        const uint32_t bt[2] = {up ? a[1] : a[0], up ? a[3] : a[2]};
        mma_bf16(st[k & 1], a[0], a[1], a[2], a[3], ones);
        mma_bf16(st[2 + (k & 1)], a[0], a[1], a[2], a[3], bt);
      }
      if (kb == 2) release_slot(sb, NS - 1, lane);
      if (kb == 0) STAMP(24 + wg);

if (kb == 8) STAMP(26 + wg);

    }
    rs0 = (st[0][0] + st[1][0]) * (1.f / D);
    rs1 = (st[0][2] + st[1][2]) * (1.f / D);
    const float qe = up ? st[2][2] + st[3][2] : st[2][0] + st[3][0], qo = up ? st[2][3] + st[3][3] : st[2][1] + st[3][1];
    if ((lane & 3) == (lane >> 3)) {
      const uint32_t q = __float_as_uint((lane & 4) ? qo : qe), off = OFF_VAR + 64 * warp + 32 * up + (lane & 28);
      const uint32_t pb = mapa(sb, up ^ 1);
      sts32(sb + off, q);
      asm volatile("st.async.weak.shared::cluster.mbarrier::complete_tx::bytes.b32 [%0], %1, [%2];"
                   ::"r"(pb + off), "r"(q), "r"(pb + B_VAR + 8 * wg) : "memory");
    }
    if (wg == 1) asm volatile("bar.arrive 6, 256;" ::: "memory");
    const uint32_t mm0 = pack_bf16(rs0, rs0), mm1 = pack_bf16(rs1, rs1);
#pragma unroll
    for (int i = 0; i < 144; i++) A[i] = sub_bf16x2(A[i], (i & 1) ? mm1 : mm0);
  }
  if (wg == 0 && SKB == 0) asm volatile("bar.sync 6, 256;" ::: "memory");
  STAMP(2 + wg);

  Ring ring{0, 0};
  const uint64_t desc0 = bdesc(sb);
#pragma unroll 1
  for (int step = 0; step < 12; step++) {
    float acc[64];
    uint32_t prev = 0;
#pragma unroll
    for (int kb = 0; kb < 9; kb++) {
      mbar_wait(sb + B_FULL + 8 * ring.slot, ring.phase);
      const uint64_t db = desc0 + (ring.off() >> 4);
      if (SKB > 0 && kb == SKB && step == 0 && wg == 0) asm volatile("bar.sync 6, 256;" ::: "memory");
      if (LAG1 == LAG2) {
        if (kb == 9 - LAG1) lag_sync(wg);
      } else {
        if (kb == 9 - LAG1 && step < 9) lag_sync(wg);
        if (kb == 9 - LAG2 && step >= 9) lag_sync(wg);
      }
      WG_FENCE();
#pragma unroll
      for (int k = 0; k < 4; k++) wgmma_rs<128, 1>(acc, &A[(kb * 4 + k) * 4], db + k * 128, kb + k);
      WG_COMMIT();
      if (kb == 8) lag_arrive(wg);
      if (kb == 0 && step > 9) stage_done(sb + B_SF + 8 * (wg * 5 + step - 10), lane);
      if (kb > 0) {
        WG_WAIT(1);
        release_slot(sb, prev, lane);
#pragma unroll
        for (int j = 0; j < 4; j++) lds128_if(&A[16 * (kb - 1) + 4 * j], priv + (kb - 1) * BOX + j * 512, step == 8);
      }
      if (kb == VKB && step == 0) {
        mbar_wait(sb + B_VAR + 8 * wg, 0);
        wg_bar(wg);
        const uint32_t va = sb + OFF_VAR + 64 * warp + (lane & 28);
        rs0 = ln_rstd(fmaxf(__uint_as_float(lds32(va)) * (1.f / D) - rs0 * rs0, 0.f));
        rs1 = ln_rstd(fmaxf(__uint_as_float(lds32(va + 32)) * (1.f / D) - rs1 * rs1, 0.f));
        if (warp == s && (lane & 3) == 0) {
          sts32(sb + OFF_MISC + 160 + lane, __float_as_uint(rs0));
          sts32(sb + OFF_MISC + 192 + lane, __float_as_uint(rs1));
        }
      }
      prev = ring.slot;
      ring.next();
    }
    if (step > 9) {
      mbar_wait(sb + B_XIN + 8 * (wg * 4 + step - 10), 0);
      mbar_wait(sb + B_SE + 8 * (wg * 3 + step - 10), 0);
    }
    WG_WAIT(0);
    release_slot(sb, prev, lane);
    if (step < 9) {
      uint32_t hp[16];
      const float c0 = 0.5f * rs0, c1 = 0.5f * rs1;
#pragma unroll
      for (int i = 0; i < 16; i++) {
        const float c = (i & 1) ? c1 : c0;
        const float g0 = acc[2 * i] * c, g1 = acc[2 * i + 1] * c;
        const float h0 = fmaf(g0, tanh_hw(g0), g0) * acc[32 + 2 * i];
        const float h1 = fmaf(g1, tanh_hw(g1), g1) * acc[33 + 2 * i];
        hp[i] = pack_bf16(h0, h1);
      }
      if (step < 8) {
#pragma unroll
        for (int j = 0; j < 4; j++) sts128(priv + step * BOX + j * 512, &hp[4 * j]);
      } else {
#pragma unroll
        for (int i = 0; i < 16; i++) A[128 + i] = hp[i];

STAMP(4 + wg);

      }
    } else {
      const int e = step - 9;
      stage_partial(acc, priv + (2 + (e & 1)) * BOX);
      uint32_t xin[16];
#pragma unroll
      for (int j = 0; j < 4; j++) lds128(&xin[4 * j], e > 0 ? priv + ((e - 1) & 1) * BOX + j * 512 : sb + OFF_ZERO);
      stage_sum(acc + 32, xin, priv + 4 * BOX);
    }
  }

STAMP(6 + wg);

  float acc[32];
  uint32_t pa[16], o8[2];
  step64<0>(acc, A, sb, desc0, ring, wg, lane, [&](int st) {
    if (st == 0) stage_done(sb + B_SF + 8 * (wg * 5 + 2), lane);
    if (st == 4) {
      mbar_wait(sb + B_XIN + 8 * (wg * 4 + 2), 0);
#pragma unroll
      for (int j = 0; j < 4; j++) lds128(&pa[4 * j], priv + j * 512);
    }
  });
  stage_sum(acc, pa, priv + 3 * BOX);
  stage_done(sb + B_SF + 8 * (wg * 5 + 3), lane);
  STAMPC(tid == 0, 12);
  step64<1>(acc, A, sb, desc0, ring, wg, lane, [&](int st) {
    if (st == B8ST) {
      const int t = fresh_tid(), d = 16 * (t >> 6) + 8 * (t & 1) + (t & 6), l = (t >> 3) & 7;
      mbar_wait(sb + B_B8, 0);
      float v[4] = {0.f, 0.f, 0.f, 0.f};
#pragma unroll
      for (int i = 0; i < 8; i++) {
        uint32_t q[2];
        lds64(q, sb + OFF_STASH + (i >> 2) * STASH_STRIDE + 6 * BOX + (i & 3) * 2048 + 8 * t);
        v[0] += bf_lo(q[0]); v[1] += bf_hi(q[0]);
        v[2] += bf_lo(q[1]); v[3] += bf_hi(q[1]);
      }
#pragma unroll
      for (int i = 0; i < 4; i++) {
        const int dd = d + (i & 1);
        const uint32_t h = lds16(sb + OFF_STASH + 7 * BOX + dd * 128 + (((2 * (s & 3) + (i >> 1)) ^ (dd & 7)) << 4) + 2 * l);
        v[i] = fmaf(v[i], __uint_as_float(lds32(sb + OFF_MISC + 160 + 32 * (i >> 1) + 4 * l)), bf_lo(h));
      }
      o8[0] = pack_bf16(v[0], v[1]);
      o8[1] = pack_bf16(v[2], v[3]);
      stage_done(sb + B_CV + 16, lane);
    }
    if (st == 3) mbar_wait(sb + B_SE + 8 * (wg * 3 + 2), 0);
  });
  stage_partial(acc, priv + 4 * BOX);
  stage_done(sb + B_SF + 8 * (wg * 5 + 4), lane);
  STAMPC(tid == 0, 13);
  step64<2>(acc, A, sb, desc0, ring, wg, lane, [&](int st) {
    if (st == 1) {
      const int t = fresh_tid(), row = (s >> 2) * 1024 + r * 64 + (s & 3) * 16 + ((t >> 3) & 7);
      uint32_t* o = reinterpret_cast<uint32_t*>(out + row * D + 512 + 16 * (t >> 6) + 8 * (t & 1) + (t & 6));
      o[0] = o8[0];
      o[4 * D] = o8[1];
      mbar_wait(sb + B_LIN + 8 * (wg * 2), 0);
    }
    if (st == XST) {
      mbar_wait(sb + B_XIN + 8 * (wg * 4 + 3), 0);
      add_packed(pa, priv + 5 * BOX, priv + BOX);
    }
    if (st == 4) {
      uint32_t pb[16];
      mbar_wait(sb + B_LIN + 8 * (wg * 2 + 1), 0);
      add_packed(pb, priv + 6 * BOX, priv);
#pragma unroll
      for (int i = 0; i < 16; i++) pa[i] = add_bf16x2(pa[i], pb[i]);
    }
  });
  STAMP(8 + wg);
  const uint32_t ob = sb + stash + 5 * BOX + w * 2048;
  __syncwarp();
#pragma unroll
  for (int i = 0; i < 4; i++) {
    uint32_t p[4];
    ldsm4t(p, sb + stash + 7 * BOX + tr_off + i * 2048);
#pragma unroll
    for (int j = 0; j < 4; j++) {
      const float rr = (j & 1) ? rs1 : rs0;
      const float lo = acc[8 * i + 2 * j] + bf_lo(pa[4 * i + j]), hi = acc[8 * i + 2 * j + 1] + bf_hi(pa[4 * i + j]);
      p[j] = add_bf16x2(p[j], pack_bf16(lo * rr, hi * rr));
    }
    stsm4(ob + (lane & 15) * 128 + (((2 * i + (lane >> 4)) ^ (lane & 7)) << 4), p);
  }
  __syncwarp();
  __nv_bfloat16* o = out + (wg * 1024 + r * 64 + w * 16 + (lane >> 3)) * D + s * 64 + (lane & 7) * 8;
#pragma unroll
  for (int i = 0; i < 4; i++) {
    const int row = 4 * i + (lane >> 3);
    uint32_t v[4];
    lds128(v, ob + row * 128 + (((lane & 7) ^ (row & 7)) << 4));
    *reinterpret_cast<uint4*>(o + 4 * i * D) = make_uint4(v[0], v[1], v[2], v[3]);
  }
  STAMP(10 + wg);
}

struct StageSrc {
  const CUtensorMap *m0, *m1;
  int x0, x1, y0, y1;
};
__device__ __forceinline__ StageSrc stage_src(int it, int s, const CUtensorMap* w1, const CUtensorMap* w3,
                                              const CUtensorMap* w2) {
  if (it < 108) {
    const int step = it / 9, kb = it - step * 9, e = step - 9;
    if (it < 81) return {w1, w3, s * 576 + step * 64, s * 576 + step * 64, kb * 64, kb * 64};
    return {w2, w2, (((s + 2 * e + 2) & 7) ^ 1) * 64, (e == 0 ? 8 : (s + 2 * e) & 7) * 64, s * 576 + kb * 64, s * 576 + kb * 64};
  }
  const int e = (it - 108) / 5, st = it - 108 - e * 5, x = (e == 0 ? (s + 6) & 7 : e == 1 ? s ^ 1 : s) * 64;
  return {w2, st < 4 ? w2 : nullptr, x, x, s * 576 + st * 128, s * 576 + st * 128 + 64};
}
__device__ __forceinline__ void prefetch_box(const CUtensorMap* m, int x, int y) {
  asm volatile("cp.async.bulk.prefetch.tensor.2d.L2.global [%0, {%1, %2}];" ::"l"(m), "r"(x), "r"(y) : "memory");
}

__device__ __forceinline__ void ffn_producer(uint32_t sb, int r, int s, int first, const CUtensorMap* w1,
                                             const CUtensorMap* w3, const CUtensorMap* w2) {
  Ring ring{(uint32_t)first, 1};
  mbar_wait(sb + B_CV + 8, 0);
#pragma unroll 1
  for (int it = first; it < 123; it++) {
    mbar_wait(sb + B_EMPTY + 8 * ring.slot, ring.slot == NS - 1 ? ring.phase ^ 1 : ring.phase);
    if (elect_one()) {
      const uint32_t bar = sb + B_FULL + 8 * ring.slot, dst = sb + ring.off();
      const StageSrc a = stage_src(it, s, w1, w3, w2);
      mbar_expect(bar, a.m1 ? SLOT : BOX);
      tma2d(dst, a.m0, a.x0, a.y0, bar);
      if (a.m1) tma2d(dst + BOX, a.m1, a.x1, a.y1, bar);
      const int nx = it + PFN;
      if (nx < 123 && ((nx ^ r) & 7) == 0) {
        const StageSrc b = stage_src(nx, s, w1, w3, w2);
        if (r < 8) prefetch_box(b.m0, b.x0, b.y0);
        else if (b.m1) prefetch_box(b.m1, b.x1, b.y1);
      }
    }
    __syncwarp();
    ring.next();
  }
  const uint32_t pb = mapa(sb, (s & 1) ^ 1);
#pragma unroll 1
  for (int wg = 0; wg < 2; wg++) {
    const uint32_t stash = OFF_STASH + wg * STASH_STRIDE;
    mbar_wait(sb + B_SF + 8 * (wg * 5 + 4), 0);
    if (elect_one()) bulk_peer(pb + stash + BOX, sb + stash + 4 * BOX, BOX, pb + B_XIN + 8 * (wg * 4 + 3));
    __syncwarp();
  }
}

__device__ __forceinline__ void ffn_sender(uint32_t sb, Scratch* g, int r, int s, int wg) {
  const uint32_t stash = OFF_STASH + wg * STASH_STRIDE, pb = mapa(sb, (s & 1) ^ 1);
  mbar_wait(sb + B_CV + 8 * wg, 0);
  STAMPC(1, 58 + wg);
  if (elect_one()) {
    asm volatile("fence.release.gpu;" ::: "memory");
    red_add(&g->epoch[32 * wg], 1);
  }
  __syncwarp();
#pragma unroll 1
  for (int e = 0; e < 4; e++) {
    mbar_wait(sb + B_SF + 8 * (wg * 5 + e), 0);
    STAMPC(e == 3 && wg == 0, 62);
    if (e == 0) {
      if (elect_one()) mbar_arrive_cluster(pb + B_PRDY + 8 * wg);
      __syncwarp();
      mbar_wait(sb + B_PRDY + 8 * wg, 0);
    }
    if (elect_one()) {
      if (e < 3) bulk_peer(pb + stash + (e & 1) * BOX, sb + stash + (2 + (e & 1)) * BOX, BOX, pb + B_XIN + 8 * (wg * 4 + e));
      const int idx = ((r * 8 + ((s + 2 * e) & 7)) * 3 + e - 1) * 2 + wg;
      uint4* dst = e == 0 ? &g->part8[((r * 8 + s) * 2 + wg) * 512] : &g->part[idx * 512];
#pragma unroll 1
      for (uint32_t q = 0, n = e == 3 ? BOX : PACE; q < BOX; q += n) {
        bulk_store(dst + (q >> 4), sb + stash + (e == 3 ? 3 : 4) * BOX + q, n);
        asm volatile("cp.async.bulk.commit_group;" ::: "memory");
        asm volatile("cp.async.bulk.wait_group.read 0;" ::: "memory");
      }
      if (e < 3) mbar_arrive(sb + B_SE + 8 * (wg * 3 + e));
      if (e != 2) {
        asm volatile("cp.async.bulk.wait_group 0;" ::: "memory");
        STAMPC(e == 3 && wg == 0, 63);
        asm volatile("fence.release.gpu;" ::: "memory");
        if (e == 0) {
#pragma unroll
          for (int q = 0; q < 4; q++) red_add(&g->flag8[r * 8 + wg * 4 + q], 1);
        } else {
          if (e == 3) red_add(&g->flag[((r * 8 + ((s + 4) & 7)) * 3 + 1) * 2 + wg], 1);
          red_add(&g->flag[idx], 1);
        }

      }
    }
    __syncwarp();
  }
  mbar_wait(sb + B_XIN + 8 * (wg * 4 + 3), 0);
  if (elect_one()) mbar_arrive_cluster(pb + B_DONE + 8 * wg);
  __syncwarp();
  mbar_wait(sb + B_DONE + 8 * wg, 0);
}

__device__ __forceinline__ void ffn_receiver(uint32_t sb, Scratch* g, int c, int r, int s, const CUtensorMap* ht,
                                             const CUtensorMap* ht3) {
  const int lane = fresh_tid() & 31;
#pragma unroll 1
  for (int h = 0; h < 2; h++) {
    wait_flag(&g->epoch[32 * h], (lds32(sb + OFF_MISC + 152) & ~127u) + 128);
    STAMPC(lane == 0 && h == 0, 31);
    mbar_wait(sb + B_CV + 8, 0);
    STAMPC(lane == 0, h ? 23 : 1);
    if (elect_one()) {
      asm volatile("fence.proxy.async.global;" ::: "memory");
      tma2d(sb + (NS - 1) * SLOT + h * BOX, ht, h * 1024 + r * 64, 0, sb + B_H + 40 * h);
#pragma unroll
      for (int i = 0; i < 4; i++)
        tma2d(sb + OFF_STASH + h * STASH_STRIDE + i * SLOT, ht3, h * 1024 + r * 64, 64 + 128 * i, sb + B_H + 40 * h + 8 + 8 * i);
    }
    __syncwarp();
  }
  if (lane < 6) g->stats[(lane >> 1) * 256 + 2 * c + (lane & 1)] = make_uint4(0, 0, 0, 0);
  mbar_wait(sb + B_SF, 0);
  mbar_wait(sb + B_SF + 40, 0);
  wait_flag(&g->flag8[r * 8 + s], 8);
  __syncwarp();
  if (elect_one()) {
    g->flag8[r * 8 + s] = 0;
    asm volatile("fence.proxy.async.global;" ::: "memory");
    tma2d(sb + OFF_STASH + 7 * BOX, ht, (s >> 2) * 1024 + r * 64, 512, sb + B_B8);
#pragma unroll 1
    for (int i = 0; i < 8; i++)
      bulk_load(sb + OFF_STASH + (i >> 2) * STASH_STRIDE + 6 * BOX + (i & 3) * 2048, &g->part8[(r * 8 + i) * 1024 + s * 128],
                2048, sb + B_B8);
  }
  __syncwarp();
  const int base = (r * 8 + s) * 6;
#pragma unroll 1
  for (int late = 0; late < 2; late++) {
    if (late) {
      mbar_wait(sb + B_CV + 16, 0);
      if (elect_one()) {
        tma2d(sb + OFF_STASH + 7 * BOX, ht, r * 64, s * 64, sb + B_LIN + 8);
        tma2d(sb + OFF_STASH + STASH_STRIDE + 7 * BOX, ht, 1024 + r * 64, s * 64, sb + B_LIN + 24);
      }
      __syncwarp();
    }
    uint32_t todo = late ? 0x3c : 0x03;
#pragma unroll 1
    for (uint32_t spins = 0; todo; spins++) {
      if (spins > SPIN_LIMIT) __trap();
      uint32_t ready = __ballot_sync(~0u, ((todo >> lane) & 1) && ld_acquire(&g->flag[base + lane]) != 0);
      __syncwarp();
      todo &= ~ready;
#pragma unroll 1
      for (; ready; ready &= ready - 1) {
        const int i = __ffs(ready) - 1, wg = i & 1, j = i >> 1;
        if (elect_one()) {
          asm volatile("fence.proxy.async.global;" ::: "memory");
          bulk_load(sb + OFF_STASH + wg * STASH_STRIDE + (j == 2 ? 0 : 5 + j) * BOX, &g->part[(base + i) * 512], BOX,
                    sb + B_LIN + 8 * (wg * 2 + late));
        }
        __syncwarp();
      }
    }
  }
  if (lane < 6) g->flag[base + lane] = 0;

}

template <uint32_t B0, uint32_t B1>
__device__ __forceinline__ void init_barriers(uint32_t sb) {
#pragma unroll
  for (uint32_t b = B0; b < B1; b += 8) mbar_init(sb + b, b == B_UX ? 2 : b < B_SF ? 1 : b < B_EMPTY ? 4 : 8);
#pragma unroll
  for (uint32_t b = B0; b < B1 && b < B_FULL; b += 8)
    mbar_expect(sb + b, b < B_PK    ? 2 * BOX
                        : b < B_LIN ? BOX
                        : b < B_H   ? ((b - B_LIN) & 8 ? 3 : 1) * BOX
                        : b < B_UX  ? ((b - B_H) % 40 ? 2 : 1) * BOX
                        : b < B_VAR ? 5 * L
                        : b < B_B8  ? 128
                                    : 3 * BOX);
}

__global__ void __launch_bounds__(384, 1)
fused_kernel(const __grid_constant__ SsmParams p, __nv_bfloat16* __restrict__ out,
             const __grid_constant__ CUtensorMap tm_w1, const __grid_constant__ CUtensorMap tm_w3,
             const __grid_constant__ CUtensorMap tm_w2, const __grid_constant__ CUtensorMap tm_ht,
             const __grid_constant__ CUtensorMap tm_ht3, const __grid_constant__ CUtensorMap tm_x) {
  extern __shared__ __align__(1024) uint8_t smem[];
  uint32_t t0;
  asm volatile("mov.u32 %0, %clock;" : "=r"(t0));
  const ModeIn in = load_modes(
      p, 9 * (blockIdx.x >> 1) + (threadIdx.x < 256 ? 5 * (blockIdx.x & 1) + (threadIdx.x >> 6) : 4), threadIdx.x & 63);
  uint32_t sb = (uint32_t)__cvta_generic_to_shared(smem);
  asm volatile("" : "+r"(sb));
  const int c = blockIdx.x, cl = c >> 1, rank = c & 1, tid = threadIdx.x, warp = warp_index(), wg = warp >> 2;
  const int s = ((cl & 1) * 2 + ((cl >> 3) & 1)) * 2 + rank, r = ((cl >> 1) & 3) * 4 + (cl >> 4);
  STAMPC(tid == 0, 0);
  Scratch* const g = p.g;
  unsigned target = 0;
  int first = 0;
  const int w = warp & 3, lane = tid & 31;
  const int ch0 = 9 * cl + 5 * rank;
  uint4 xv[9];
  if (wg == 2) {
    const uint4* xr = reinterpret_cast<const uint4*>(p.x) + (16 * c + ((tid & 127) >> 3)) * (D / 8) + (tid & 7);
    for (uint32_t now = t0; now - t0 < XDELAY;) asm volatile("mov.u32 %0, %clock;" : "=r"(now));
#pragma unroll
    for (int i = 0; i < 9; i++)
      asm volatile("ld.global.nc.v4.u32 {%0,%1,%2,%3}, [%4];"
                   : "=r"(xv[i].x), "=r"(xv[i].y), "=r"(xv[i].z), "=r"(xv[i].w) : "l"(xr + 8 * i));
  }
  const uint32_t dsk = ldg16(p.dskip + min(ch0 + (tid & 7), D - 1));
  if (tid == 8) asm volatile("ld.relaxed.gpu.global.u32 %0, [%1];" : "=r"(target) : "l"(&g->epoch[32]) : "memory");
  STAMP(38 + wg);
  if (warp == 9) {
    const uint32_t z[4] = {0, 0, 0, 0};
    sts128(sb + OFF_ZERO, z);
#pragma unroll 1
    for (int i = 0; i < 5; i++)
    {
      if (lane < 26) sts128(sb + (lane < 24 ? OFF_U + i * U_PITCH : OFF_PK - 384 + i * PK_PITCH) + lane * 16, z);
    }
  }
  if (warp == 10 && elect_one()) {
    init_barriers<B_PK, B_END>(sb);
    asm volatile("fence.mbarrier_init.release.cluster;" ::: "memory");
  }
  if (warp == 8 && elect_one()) {
    asm volatile("prefetch.tensormap [%0];" ::"l"(&tm_x) : "memory");
    init_barriers<B_G, B_PK>(sb);
    asm volatile("fence.mbarrier_init.release.cluster;" ::: "memory");
    for (uint32_t now = t0; now - t0 < GDELAY;) asm volatile("mov.u32 %0, %clock;" : "=r"(now));
#pragma unroll
    for (int i = 0; i < 2; i++)
      asm volatile(
          "cp.async.bulk.tensor.5d.shared::cluster.global.mbarrier::complete_tx::bytes [%0], [%1, {%3, %4, %4, %4, %5}], [%2];"
          ::"r"(sb + OFF_G + i * SLOT), "l"(&tm_x), "r"(sb + B_G + 8 * i), "r"((9 * cl) & ~7), "r"(0), "r"(32 * rank + 16 * i)
          : "memory");
  }
  __syncwarp();
  asm volatile("barrier.cluster.arrive.relaxed.aligned;" ::: "memory");
  STAMPC(tid == 256, 41);
  if (wg == 2) {
    ln1_stats(sb, g, c, xv);
    STAMP(14);
    asm volatile("barrier.cluster.wait.aligned;" ::: "memory");
    x_transpose(sb, c, w);
    STAMP(18);
  }
  const int ntask = wg < 2 ? 2 : 1 - rank;
  if (wg < 2 || rank == 1) {
    float acc[6][4];
#pragma unroll
    for (int i = 0; i < 6; i++) acc[i][0] = acc[i][1] = acc[i][2] = acc[i][3] = 0.f;
#pragma unroll 1
    for (int k = wg >> 1; k < 2; k++) {
      kgen_modes(sb + OFF_WS + wg * WS_BYTES + w * WS_WARP, in, (wg == 2 ? w >> 1 : k) ? 0x3244 : 0x1044, acc);
      STAMP(46 + wg * 2 + k);
    }
    uint32_t st[12];
    if (wg < 2) asm volatile("barrier.cluster.wait.aligned;" ::: "memory");
    kgen_finish(sb, g, wg, acc, st);
    STAMP(52 + wg);
    if (wg < 2) {
      if (tid < 9) sts32(sb + OFF_MISC + 120 + 4 * tid, tid < 8 ? dsk * 0x10001u : target);
      ln1_apply(sb, g, st);
      asm volatile("fence.proxy.async.shared::cta;\nbar.arrive 6, 384;\nbar.sync 4, 256;" ::: "memory");
    } else {
      asm volatile("fence.proxy.async.shared::cta;" ::: "memory");
      wg_bar(2);
      if (w == 2 && elect_one()) {
        const uint32_t pb = mapa(sb, 0), off = OFF_PK + 4 * PK_PITCH + 32;
        bulk_peer(pb + off, sb + off, BOX, pb + B_PK);
      }
      __syncwarp();
    }
  }
  if (wg == 2) {
    asm volatile("bar.sync 6, 384;" ::: "memory");
    mbar_wait(sb + B_UX, 0);
    if (w == 0 && elect_one()) {
#pragma unroll 1
      for (int i = 0; i < EARLY; i++) {
        const uint32_t bar = sb + B_FULL + 8 * i, dst = sb + i * SLOT;
        mbar_expect(bar, SLOT);
        tma2d(dst, &tm_w1, s * 576, i * 64, bar);
        tma2d(dst + BOX, &tm_w3, s * 576, i * 64, bar);
      }
      asm volatile("prefetch.tensormap [%0];" ::"l"(&tm_ht) : "memory");
      asm volatile("prefetch.tensormap [%0];" ::"l"(&tm_ht3) : "memory");
    }
    if (w == 1 && elect_one()) {
#pragma unroll 1
      for (int i = EARLY + ((r - EARLY) & 7); i < EARLY + PFN; i += 8)
        prefetch_box(r < 8 ? &tm_w1 : &tm_w3, s * 576 + (i / 9) * 64, (i % 9) * 64);
    }
    __syncwarp();
    STAMP(55);
  }
  first = EARLY;
  STAMPC(tid == 0, 19);
#pragma unroll 1
  for (int k = 0; k < ntask; k++) {
    const int local = wg == 2 ? 3 : 2 * wg + k + (wg & k & (rank ^ 1));
    if (local == 4) mbar_wait(sb + B_PK, 0);
    conv_task(sb, g, wg, w, local, ch0 + local, k);
  }
  STAMP(20 + wg);
  asm volatile("fence.proxy.async.shared::cta;" ::: "memory");
  __syncwarp();
  if (wg == 2) wg_bar(2);
  else if (elect_one()) mbar_arrive(sb + B_CV + 8);
  __syncwarp();

  if (wg < 2) {
    asm volatile("setmaxnreg.inc.sync.aligned.u32 240;");
    ffn_consumer(sb, g, warp, r, s, out);
  } else {
    asm volatile("setmaxnreg.dec.sync.aligned.u32 24;");
    const int hw = warp & 3;
    if (hw == 0) ffn_producer(sb, r, s, first, &tm_w1, &tm_w3, &tm_w2);
    else if (hw < 3) ffn_sender(sb, g, r, s, hw - 1);
    else ffn_receiver(sb, g, c, r, s, &tm_ht, &tm_ht3);
  }
}

typedef CUresult (*EncodeFn)(CUtensorMap*, CUtensorMapDataType, cuuint32_t, void*, const cuuint64_t*, const cuuint64_t*,
                             const cuuint32_t*, const cuuint32_t*, CUtensorMapInterleave, CUtensorMapSwizzle,
                             CUtensorMapL2promotion, CUtensorMapFloatOOBfill);

void make_map(EncodeFn enc, CUtensorMap* m, void* p, uint64_t cols, uint64_t rows, uint32_t box_rows = 64) {
  cuuint64_t dims[2] = {cols, rows}, strides[1] = {cols * 2};
  cuuint32_t box[2] = {64, box_rows}, es[2] = {1, 1};
  enc(m, CU_TENSOR_MAP_DATA_TYPE_BFLOAT16, 2, p, dims, strides, box, es, CU_TENSOR_MAP_INTERLEAVE_NONE,
      CU_TENSOR_MAP_SWIZZLE_128B, CU_TENSOR_MAP_L2_PROMOTION_L2_128B, CU_TENSOR_MAP_FLOAT_OOB_FILL_NONE);
}

}

extern "C" void kernel_launch(void* const* d_in, const int* in_sizes, int n_in, void* d_out, int out_size) {
  typedef const __nv_bfloat16* P;
  void* fn = nullptr;
  cudaDriverEntryPointQueryResult qr;
  cudaGetDriverEntryPoint("cuTensorMapEncodeTiled", &fn, cudaEnableDefault, &qr);
  EncodeFn enc = (EncodeFn)fn;
  void* hT = nullptr;
  cudaGetSymbolAddress(&hT, g_scratch);
  CUtensorMap m1, m3, m2, mh, mh3, mx;
  make_map(enc, &m1, d_in[10], F, D);
  make_map(enc, &m3, d_in[11], F, D);
  make_map(enc, &m2, d_in[12], D, F);
  make_map(enc, &mh, hT, L, D);
  make_map(enc, &mh3, hT, L, D, 128);
  {
    cuuint64_t dims[5] = {D, 2, 4, 4, 64}, strides[4] = {D * 2, D * 16, D * 4, D * 64};
    cuuint32_t box[5] = {16, 2, 4, 4, 16}, es[5] = {1, 1, 1, 1, 1};
    enc(&mx, CU_TENSOR_MAP_DATA_TYPE_BFLOAT16, 5, d_in[0], dims, strides, box, es, CU_TENSOR_MAP_INTERLEAVE_NONE,
        CU_TENSOR_MAP_SWIZZLE_32B, CU_TENSOR_MAP_L2_PROMOTION_L2_128B, CU_TENSOR_MAP_FLOAT_OOB_FILL_NONE);
  }
  SsmParams p = {(P)d_in[1], (P)d_in[2], (P)d_in[3], (P)d_in[4], (P)d_in[5], (P)d_in[6],
                 (P)d_in[7], (P)d_in[0], (P)d_in[8], (Scratch*)hT};
  cudaFuncSetAttribute(fused_kernel, cudaFuncAttributeMaxDynamicSharedMemorySize, SMEM_BYTES);
  cudaLaunchConfig_t cfg = {};
  cfg.gridDim = dim3(128);
  cfg.blockDim = dim3(384);
  cfg.dynamicSmemBytes = SMEM_BYTES;
  cfg.stream = cudaStreamPerThread;
  cudaLaunchAttribute at[1];
  at[0].id = cudaLaunchAttributeClusterDimension;
  at[0].val.clusterDim.x = 2;
  at[0].val.clusterDim.y = 1;
  at[0].val.clusterDim.z = 1;
  cfg.attrs = at;
  cfg.numAttrs = 1;
  cudaLaunchKernelEx(&cfg, fused_kernel, p, (__nv_bfloat16*)d_out, m1, m3, m2, mh, mh3, mx);
}
```

```cpp
#include <cuda_runtime.h>
#include <cuda_bf16.h>
#include <cuda.h>
#include <stdint.h>

namespace {

constexpr int L = 2048, D = 576, F = 4608, NMODE = 128;
constexpr int NS = 6;
constexpr int LAG = 4, LAG3 = 3;
constexpr int SKB = 1, VKB = 4;
constexpr int RKB = 4;
constexpr int B8ST = 1, LLST = 0;
constexpr int PFN = 40;
constexpr uint32_t PACE = 4096, PACE3 = 2048;
constexpr uint32_t XDELAY = 700;
constexpr uint32_t SLOT = 16384, BOX = 8192;
constexpr uint32_t OFF_STASH = NS * SLOT, STASH_STRIDE = 8 * BOX;
constexpr uint32_t OFF_BAR = NS * SLOT + 16 * BOX;
constexpr uint32_t B_G = OFF_BAR;
constexpr uint32_t B_PK = B_G + 8 * 2;
constexpr uint32_t B_XIN = B_PK + 8;
constexpr uint32_t B_LIN = B_XIN + 8 * 8;
constexpr uint32_t B_H = B_LIN + 8 * 2;
constexpr uint32_t B_UX = B_H + 8 * 10;
constexpr uint32_t B_VAR = B_UX + 8;
constexpr uint32_t B_B8 = B_VAR + 16;
constexpr uint32_t B_FULL = B_B8 + 8;
constexpr uint32_t B_SE = B_FULL + 8 * NS;
constexpr uint32_t B_XL = B_SE + 8 * 6;
constexpr uint32_t B_PRDY = B_XL + 8;
constexpr uint32_t B_DONE = B_PRDY + 8 * 2;
constexpr uint32_t B_SF = B_DONE + 8 * 2;
constexpr uint32_t B_EMPTY = B_SF + 8 * 10;
constexpr uint32_t B_CV = B_EMPTY + 8 * NS;
constexpr uint32_t B_END = B_CV + 8 * 3;
constexpr uint32_t OFF_DSK = OFF_BAR + 512, OFF_ZERO = OFF_DSK + 48, OFF_RS = OFF_ZERO + 16;
constexpr uint32_t OFF_VAR = OFF_BAR + 640, OFF_RES8 = OFF_BAR + 1024;
constexpr uint32_t SMEM_BYTES = OFF_RES8 + 2048;
constexpr uint32_t SPIN_LIMIT = 1u << 24;
static_assert(B_END <= OFF_BAR + 512, "barrier region");

constexpr uint32_t EARLY = 4;
constexpr uint32_t OFF_G = 0;
constexpr uint32_t OFF_WS = 2 * SLOT, WS_WARP = 7168, WS_KC = 4 * WS_WARP + 16, KC_PITCH = 1312, WS_BYTES = 32768;
constexpr uint32_t OFF_PART = EARLY * SLOT;
constexpr uint32_t OFF_U = OFF_WS + 3 * WS_BYTES, U_PAD = 384, U_PITCH = U_PAD + 4096;
constexpr uint32_t OFF_X = OFF_U + 5 * U_PITCH, X_PITCH = 4160;
constexpr uint32_t OFF_PK = OFF_X + 5 * X_PITCH, PK_PITCH = 8224;
constexpr uint32_t OFF_STG = OFF_PK + 5 * PK_PITCH, STG_PITCH = 2112;
static_assert(OFF_STG + 5 * STG_PITCH <= OFF_BAR, "front region");
static_assert(WS_KC + 2 * KC_PITCH <= WS_BYTES, "scratch");

struct Scratch {
  __nv_bfloat16 hT[D * L];
  uint4 part[16 * 8 * 2 * 2 * 512];
  uint4 last[16 * 8 * 2 * 512];
  uint4 part8[16 * 8 * 2 * 512];
  uint4 stats[3 * 256];
  unsigned flag[16 * 8 * 2 * 2];
  unsigned flag8[16 * 8 * 32];
  unsigned epoch[64];
};
__device__ __align__(1024) Scratch g_scratch;

__device__ __forceinline__ int fresh_tid() {
  int t;
  asm volatile("mov.u32 %0, %tid.x;" : "=r"(t));
  return t;
}
__device__ __forceinline__ int warp_index() { return __shfl_sync(~0u, fresh_tid() >> 5, 0); }
__device__ __forceinline__ void mbar_init(uint32_t b, uint32_t c) {
  asm volatile("mbarrier.init.shared::cta.b64 [%0], %1;" ::"r"(b), "r"(c));
}
__device__ __forceinline__ void mbar_expect(uint32_t b, uint32_t n) {
  asm volatile("mbarrier.arrive.expect_tx.shared::cta.b64 _, [%0], %1;" ::"r"(b), "r"(n) : "memory");
}
__device__ __forceinline__ void mbar_arrive(uint32_t b) {
  asm volatile("mbarrier.arrive.shared::cta.b64 _, [%0];" ::"r"(b) : "memory");
}
__device__ __forceinline__ void mbar_arrive_cluster(uint32_t b) {
  asm volatile("mbarrier.arrive.shared::cluster.b64 _, [%0];" ::"r"(b) : "memory");
}
__device__ __forceinline__ void mbar_wait(uint32_t b, uint32_t parity) {
  asm volatile(
      "{\n.reg .pred p;\n.reg .u32 c;\nmov.u32 c, 0;\n"
      "WAIT:\nmbarrier.try_wait.parity.shared::cta.b64 p, [%0], %1;\n@p bra DONE;\n"
      "add.u32 c, c, 1;\nsetp.lt.u32 p, c, %2;\n@p bra WAIT;\ntrap;\nDONE:\n}\n" ::"r"(b), "r"(parity), "n"(SPIN_LIMIT) : "memory");
}
__device__ __forceinline__ uint32_t mbar_test(uint32_t b, uint32_t parity = 0) {
  uint32_t ok;
  asm volatile("{\n.reg .pred p;\nmbarrier.test_wait.parity.shared::cta.b64 p, [%1], %2;\nselp.u32 %0, 1, 0, p;\n}\n"
               : "=r"(ok) : "r"(b), "r"(parity) : "memory");
  return ok;
}
__device__ __forceinline__ bool elect_one() {
  uint32_t p;
  asm volatile("{\n.reg .pred p;\nelect.sync _|p, 0xffffffff;\nselp.u32 %0, 1, 0, p;\n}\n" : "=r"(p));
  return p != 0;
}
__device__ __forceinline__ void tma2d(uint32_t dst, const CUtensorMap* m, int c0, int c1, uint32_t bar) {
  asm volatile("cp.async.bulk.tensor.2d.shared::cluster.global.mbarrier::complete_tx::bytes [%0], [%1, {%3, %4}], [%2];"
               ::"r"(dst), "l"(m), "r"(bar), "r"(c0), "r"(c1) : "memory");
}
__device__ __forceinline__ void bulk_load(uint32_t dst, const void* src, uint32_t bytes, uint32_t bar) {
  asm volatile("cp.async.bulk.shared::cluster.global.mbarrier::complete_tx::bytes [%0], [%1], %2, [%3];"
               ::"r"(dst), "l"(src), "r"(bytes), "r"(bar) : "memory");
}
__device__ __forceinline__ void bulk_store(void* dst, uint32_t src, uint32_t bytes) {
  asm volatile("cp.async.bulk.global.shared::cta.bulk_group [%0], [%1], %2;" ::"l"(dst), "r"(src), "r"(bytes) : "memory");
}
__device__ __forceinline__ void ldsm4t(uint32_t* r, uint32_t a) {
  asm volatile("ldmatrix.sync.aligned.m8n8.x4.trans.shared.b16 {%0,%1,%2,%3}, [%4];"
               : "=r"(r[0]), "=r"(r[1]), "=r"(r[2]), "=r"(r[3]) : "r"(a) : "memory");
}
__device__ __forceinline__ void ldsm2t(uint32_t* r, uint32_t a) {
  asm volatile("ldmatrix.sync.aligned.m8n8.x2.trans.shared.b16 {%0,%1}, [%2];" : "=r"(r[0]), "=r"(r[1]) : "r"(a) : "memory");
}
__device__ __forceinline__ void bulk_peer(uint32_t dst, uint32_t src, uint32_t bytes, uint32_t bar) {
  asm volatile("cp.async.bulk.shared::cluster.shared::cta.mbarrier::complete_tx::bytes [%0], [%1], %2, [%3];"
               ::"r"(dst), "r"(src), "r"(bytes), "r"(bar) : "memory");
}
__device__ __forceinline__ uint32_t mapa(uint32_t a, uint32_t rank) {
  uint32_t r;
  asm("mapa.shared::cluster.u32 %0, %1, %2;" : "=r"(r) : "r"(a), "r"(rank));
  return r;
}
__device__ __forceinline__ uint32_t lds32(uint32_t a) {
  uint32_t r;
  asm volatile("ld.shared.b32 %0, [%1];" : "=r"(r) : "r"(a) : "memory");
  return r;
}
__device__ __forceinline__ uint32_t lds16(uint32_t a) {
  uint32_t r;
  asm volatile("ld.shared.u16 %0, [%1];" : "=r"(r) : "r"(a) : "memory");
  return r;
}
__device__ __forceinline__ void lds64(uint32_t* r, uint32_t a) {
  asm volatile("ld.shared.v2.b32 {%0,%1}, [%2];" : "=r"(r[0]), "=r"(r[1]) : "r"(a) : "memory");
}
__device__ __forceinline__ void sts32(uint32_t a, uint32_t v) {
  asm volatile("st.shared.b32 [%0], %1;" ::"r"(a), "r"(v) : "memory");
}
__device__ __forceinline__ void sts16(uint32_t a, uint32_t v) {
  asm volatile("st.shared.u16 [%0], %1;" ::"r"(a), "r"(v) : "memory");
}
__device__ __forceinline__ void mma_bf16(float* c, uint32_t a0, uint32_t a1, uint32_t a2, uint32_t a3, const uint32_t* b) {
  asm volatile("mma.sync.aligned.m16n8k16.row.col.f32.bf16.bf16.f32 {%0,%1,%2,%3}, {%4,%5,%6,%7}, {%8,%9}, {%0,%1,%2,%3};"
               : "+f"(c[0]), "+f"(c[1]), "+f"(c[2]), "+f"(c[3])
               : "r"(a0), "r"(a1), "r"(a2), "r"(a3), "r"(b[0]), "r"(b[1]));
}
__device__ __forceinline__ void wg_bar(int wg) { asm volatile("bar.sync %0, 128;" ::"r"(wg + 1) : "memory"); }
__device__ __forceinline__ void stsm4(uint32_t a, const uint32_t* r) {
  asm volatile("stmatrix.sync.aligned.m8n8.x4.shared.b16 [%0], {%1,%2,%3,%4};"
               ::"r"(a), "r"(r[0]), "r"(r[1]), "r"(r[2]), "r"(r[3]) : "memory");
}
__device__ __forceinline__ void sts128(uint32_t a, const uint32_t* r) {
  asm volatile("st.shared.v4.b32 [%0], {%1,%2,%3,%4};" ::"r"(a), "r"(r[0]), "r"(r[1]), "r"(r[2]), "r"(r[3]) : "memory");
}
__device__ __forceinline__ void lds128(uint32_t* r, uint32_t a) {
  asm volatile("ld.shared.v4.b32 {%0,%1,%2,%3}, [%4];" : "=r"(r[0]), "=r"(r[1]), "=r"(r[2]), "=r"(r[3]) : "r"(a) : "memory");
}
__device__ __forceinline__ uint32_t pack_bf16(float lo, float hi) {
  uint32_t r;
  asm("cvt.rn.bf16x2.f32 %0, %1, %2;" : "=r"(r) : "f"(hi), "f"(lo));
  return r;
}
__device__ __forceinline__ float bf_lo(uint32_t v) { return __uint_as_float(v << 16); }
__device__ __forceinline__ float bf_hi(uint32_t v) { return __uint_as_float(v & 0xffff0000u); }
__device__ __forceinline__ float round_bf16(float v) { return __uint_as_float(pack_bf16(0.f, v)); }
__device__ __forceinline__ uint32_t sub_bf16x2(uint32_t a, uint32_t b) {
  uint32_t r;
  asm("sub.rn.bf16x2 %0, %1, %2;" : "=r"(r) : "r"(a), "r"(b));
  return r;
}
__device__ __forceinline__ uint32_t add_bf16x2(uint32_t a, uint32_t b) {
  uint32_t r;
  asm("add.rn.bf16x2 %0, %1, %2;" : "=r"(r) : "r"(a), "r"(b));
  return r;
}
__device__ __forceinline__ uint32_t mul_bf16x2(uint32_t a, uint32_t b) {
  uint32_t r;
  asm("mul.rn.bf16x2 %0, %1, %2;" : "=r"(r) : "r"(a), "r"(b));
  return r;
}
__device__ __forceinline__ uint32_t fma_bf16x2(uint32_t a, uint32_t b, uint32_t c) {
  uint32_t r;
  asm("fma.rn.bf16x2 %0, %1, %2, %3;" : "=r"(r) : "r"(a), "r"(b), "r"(c));
  return r;
}
__device__ __forceinline__ float ln_rstd(float var) {
  float sd, r;
  asm("sqrt.approx.ftz.f32 %0, %1;" : "=f"(sd) : "f"(round_bf16(round_bf16(var) + 1e-5f)));
  asm("rcp.approx.ftz.f32 %0, %1;" : "=f"(r) : "f"(round_bf16(sd)));
  return r;
}
__device__ __forceinline__ float tanh_hw(float x) {
  float r;
  asm("tanh.approx.f32 %0, %1;" : "=f"(r) : "f"(x));
  return r;
}
__device__ __forceinline__ unsigned ld_acquire(const unsigned* p) {
  unsigned v;
  asm volatile("ld.acquire.gpu.global.u32 %0, [%1];" : "=r"(v) : "l"(p) : "memory");
  return v;
}
__device__ __forceinline__ void wait_flag(const unsigned* p, unsigned target) {
  uint32_t c = 0;
  while ((int)(ld_acquire(p) - target) < 0) {
    if (++c > SPIN_LIMIT) __trap();
  }
}
__device__ __forceinline__ void red_add(unsigned* p, unsigned v) {
  asm volatile("red.relaxed.gpu.global.add.u32 [%0], %1;" ::"l"(p), "r"(v) : "memory");
}
#define WG_FENCE() asm volatile("wgmma.fence.sync.aligned;" ::: "memory")
#define WG_COMMIT() asm volatile("wgmma.commit_group.sync.aligned;" ::: "memory")
#define WG_WAIT(n) asm volatile("wgmma.wait_group.sync.aligned %0;" ::"n"(n) : "memory")

template <int TB>
__device__ __forceinline__ void wgmma_n16(float* d, const uint32_t* a, uint64_t db, int accum) {
  asm volatile(
      "{\n.reg .pred p;\nsetp.ne.b32 p, %13, 0;\n"
      "wgmma.mma_async.sync.aligned.m64n16k16.f32.bf16.bf16 "
      "{%0,%1,%2,%3,%4,%5,%6,%7}, "
      "{%8,%9,%10,%11}, %12, p, 1, 1, %14;\n}\n"
      : "+f"(d[0]), "+f"(d[1]), "+f"(d[2]), "+f"(d[3]), "+f"(d[4]), "+f"(d[5]), "+f"(d[6]), "+f"(d[7])
      : "r"(a[0]), "r"(a[1]), "r"(a[2]), "r"(a[3]), "l"(db), "r"(accum), "n"(TB));
}
template <int TB>
__device__ __forceinline__ void wgmma_n32(float* d, const uint32_t* a, uint64_t db, int accum) {
  asm volatile(
      "{\n.reg .pred p;\nsetp.ne.b32 p, %21, 0;\n"
      "wgmma.mma_async.sync.aligned.m64n32k16.f32.bf16.bf16 "
      "{%0,%1,%2,%3,%4,%5,%6,%7,%8,%9,%10,%11,%12,%13,%14,%15}, "
      "{%16,%17,%18,%19}, %20, p, 1, 1, %22;\n}\n"
      : "+f"(d[0]), "+f"(d[1]), "+f"(d[2]), "+f"(d[3]), "+f"(d[4]), "+f"(d[5]), "+f"(d[6]), "+f"(d[7]),
        "+f"(d[8]), "+f"(d[9]), "+f"(d[10]), "+f"(d[11]), "+f"(d[12]), "+f"(d[13]), "+f"(d[14]), "+f"(d[15])
      : "r"(a[0]), "r"(a[1]), "r"(a[2]), "r"(a[3]), "l"(db), "r"(accum), "n"(TB));
}
template <int TB>
__device__ __forceinline__ void wgmma_n48(float* d, const uint32_t* a, uint64_t db, int accum) {
  asm volatile(
      "{\n.reg .pred p;\nsetp.ne.b32 p, %29, 0;\n"
      "wgmma.mma_async.sync.aligned.m64n48k16.f32.bf16.bf16 "
      "{%0,%1,%2,%3,%4,%5,%6,%7,%8,%9,%10,%11,%12,%13,%14,%15,%16,%17,%18,%19,%20,%21,%22,%23}, "
      "{%24,%25,%26,%27}, %28, p, 1, 1, %30;\n}\n"
      : "+f"(d[0]), "+f"(d[1]), "+f"(d[2]), "+f"(d[3]), "+f"(d[4]), "+f"(d[5]), "+f"(d[6]), "+f"(d[7]),
        "+f"(d[8]), "+f"(d[9]), "+f"(d[10]), "+f"(d[11]), "+f"(d[12]), "+f"(d[13]), "+f"(d[14]), "+f"(d[15]),
        "+f"(d[16]), "+f"(d[17]), "+f"(d[18]), "+f"(d[19]), "+f"(d[20]), "+f"(d[21]), "+f"(d[22]), "+f"(d[23])
      : "r"(a[0]), "r"(a[1]), "r"(a[2]), "r"(a[3]), "l"(db), "r"(accum), "n"(TB));
}
template <int TB>
__device__ __forceinline__ void wgmma_n64(float* d, const uint32_t* a, uint64_t db, int accum) {
  asm volatile(
      "{\n.reg .pred p;\nsetp.ne.b32 p, %37, 0;\n"
      "wgmma.mma_async.sync.aligned.m64n64k16.f32.bf16.bf16 "
      "{%0,%1,%2,%3,%4,%5,%6,%7,%8,%9,%10,%11,%12,%13,%14,%15,%16,%17,%18,%19,%20,%21,%22,%23,%24,%25,%26,%27,%28,%29,%30,%31}, "
      "{%32,%33,%34,%35}, %36, p, 1, 1, %38;\n}\n"
      : "+f"(d[0]), "+f"(d[1]), "+f"(d[2]), "+f"(d[3]), "+f"(d[4]), "+f"(d[5]), "+f"(d[6]), "+f"(d[7]),
        "+f"(d[8]), "+f"(d[9]), "+f"(d[10]), "+f"(d[11]), "+f"(d[12]), "+f"(d[13]), "+f"(d[14]), "+f"(d[15]),
        "+f"(d[16]), "+f"(d[17]), "+f"(d[18]), "+f"(d[19]), "+f"(d[20]), "+f"(d[21]), "+f"(d[22]), "+f"(d[23]),
        "+f"(d[24]), "+f"(d[25]), "+f"(d[26]), "+f"(d[27]), "+f"(d[28]), "+f"(d[29]), "+f"(d[30]), "+f"(d[31])
      : "r"(a[0]), "r"(a[1]), "r"(a[2]), "r"(a[3]), "l"(db), "r"(accum), "n"(TB));
}
template <int TB>
__device__ __forceinline__ void wgmma_n80(float* d, const uint32_t* a, uint64_t db, int accum) {
  asm volatile(
      "{\n.reg .pred p;\nsetp.ne.b32 p, %45, 0;\n"
      "wgmma.mma_async.sync.aligned.m64n80k16.f32.bf16.bf16 "
      "{%0,%1,%2,%3,%4,%5,%6,%7,%8,%9,%10,%11,%12,%13,%14,%15,%16,%17,%18,%19,%20,%21,%22,%23,%24,%25,%26,%27,%28,%29,%30,%31,%32,%33,%34,%35,%36,%37,%38,%39}, "
      "{%40,%41,%42,%43}, %44, p, 1, 1, %46;\n}\n"
      : "+f"(d[0]), "+f"(d[1]), "+f"(d[2]), "+f"(d[3]), "+f"(d[4]), "+f"(d[5]), "+f"(d[6]), "+f"(d[7]),
        "+f"(d[8]), "+f"(d[9]), "+f"(d[10]), "+f"(d[11]), "+f"(d[12]), "+f"(d[13]), "+f"(d[14]), "+f"(d[15]),
        "+f"(d[16]), "+f"(d[17]), "+f"(d[18]), "+f"(d[19]), "+f"(d[20]), "+f"(d[21]), "+f"(d[22]), "+f"(d[23]),
        "+f"(d[24]), "+f"(d[25]), "+f"(d[26]), "+f"(d[27]), "+f"(d[28]), "+f"(d[29]), "+f"(d[30]), "+f"(d[31]),
        "+f"(d[32]), "+f"(d[33]), "+f"(d[34]), "+f"(d[35]), "+f"(d[36]), "+f"(d[37]), "+f"(d[38]), "+f"(d[39])
      : "r"(a[0]), "r"(a[1]), "r"(a[2]), "r"(a[3]), "l"(db), "r"(accum), "n"(TB));
}
template <int TB>
__device__ __forceinline__ void wgmma_n96(float* d, const uint32_t* a, uint64_t db, int accum) {
  asm volatile(
      "{\n.reg .pred p;\nsetp.ne.b32 p, %53, 0;\n"
      "wgmma.mma_async.sync.aligned.m64n96k16.f32.bf16.bf16 "
      "{%0,%1,%2,%3,%4,%5,%6,%7,%8,%9,%10,%11,%12,%13,%14,%15,%16,%17,%18,%19,%20,%21,%22,%23,%24,%25,%26,%27,%28,%29,%30,%31,%32,%33,%34,%35,%36,%37,%38,%39,%40,%41,%42,%43,%44,%45,%46,%47}, "
      "{%48,%49,%50,%51}, %52, p, 1, 1, %54;\n}\n"
      : "+f"(d[0]), "+f"(d[1]), "+f"(d[2]), "+f"(d[3]), "+f"(d[4]), "+f"(d[5]), "+f"(d[6]), "+f"(d[7]),
        "+f"(d[8]), "+f"(d[9]), "+f"(d[10]), "+f"(d[11]), "+f"(d[12]), "+f"(d[13]), "+f"(d[14]), "+f"(d[15]),
        "+f"(d[16]), "+f"(d[17]), "+f"(d[18]), "+f"(d[19]), "+f"(d[20]), "+f"(d[21]), "+f"(d[22]), "+f"(d[23]),
        "+f"(d[24]), "+f"(d[25]), "+f"(d[26]), "+f"(d[27]), "+f"(d[28]), "+f"(d[29]), "+f"(d[30]), "+f"(d[31]),
        "+f"(d[32]), "+f"(d[33]), "+f"(d[34]), "+f"(d[35]), "+f"(d[36]), "+f"(d[37]), "+f"(d[38]), "+f"(d[39]),
        "+f"(d[40]), "+f"(d[41]), "+f"(d[42]), "+f"(d[43]), "+f"(d[44]), "+f"(d[45]), "+f"(d[46]), "+f"(d[47])
      : "r"(a[0]), "r"(a[1]), "r"(a[2]), "r"(a[3]), "l"(db), "r"(accum), "n"(TB));
}
template <int TB>
__device__ __forceinline__ void wgmma_n112(float* d, const uint32_t* a, uint64_t db, int accum) {
  asm volatile(
      "{\n.reg .pred p;\nsetp.ne.b32 p, %61, 0;\n"
      "wgmma.mma_async.sync.aligned.m64n112k16.f32.bf16.bf16 "
      "{%0,%1,%2,%3,%4,%5,%6,%7,%8,%9,%10,%11,%12,%13,%14,%15,%16,%17,%18,%19,%20,%21,%22,%23,%24,%25,%26,%27,%28,%29,%30,%31,%32,%33,%34,%35,%36,%37,%38,%39,%40,%41,%42,%43,%44,%45,%46,%47,%48,%49,%50,%51,%52,%53,%54,%55}, "
      "{%56,%57,%58,%59}, %60, p, 1, 1, %62;\n}\n"
      : "+f"(d[0]), "+f"(d[1]), "+f"(d[2]), "+f"(d[3]), "+f"(d[4]), "+f"(d[5]), "+f"(d[6]), "+f"(d[7]),
        "+f"(d[8]), "+f"(d[9]), "+f"(d[10]), "+f"(d[11]), "+f"(d[12]), "+f"(d[13]), "+f"(d[14]), "+f"(d[15]),
        "+f"(d[16]), "+f"(d[17]), "+f"(d[18]), "+f"(d[19]), "+f"(d[20]), "+f"(d[21]), "+f"(d[22]), "+f"(d[23]),
        "+f"(d[24]), "+f"(d[25]), "+f"(d[26]), "+f"(d[27]), "+f"(d[28]), "+f"(d[29]), "+f"(d[30]), "+f"(d[31]),
        "+f"(d[32]), "+f"(d[33]), "+f"(d[34]), "+f"(d[35]), "+f"(d[36]), "+f"(d[37]), "+f"(d[38]), "+f"(d[39]),
        "+f"(d[40]), "+f"(d[41]), "+f"(d[42]), "+f"(d[43]), "+f"(d[44]), "+f"(d[45]), "+f"(d[46]), "+f"(d[47]),
        "+f"(d[48]), "+f"(d[49]), "+f"(d[50]), "+f"(d[51]), "+f"(d[52]), "+f"(d[53]), "+f"(d[54]), "+f"(d[55])
      : "r"(a[0]), "r"(a[1]), "r"(a[2]), "r"(a[3]), "l"(db), "r"(accum), "n"(TB));
}
template <int TB>
__device__ __forceinline__ void wgmma_n128(float* d, const uint32_t* a, uint64_t db, int accum) {
  asm volatile(
      "{\n.reg .pred p;\nsetp.ne.b32 p, %69, 0;\n"
      "wgmma.mma_async.sync.aligned.m64n128k16.f32.bf16.bf16 "
      "{%0,%1,%2,%3,%4,%5,%6,%7,%8,%9,%10,%11,%12,%13,%14,%15,%16,%17,%18,%19,%20,%21,%22,%23,%24,%25,%26,%27,%28,%29,%30,%31,%32,%33,%34,%35,%36,%37,%38,%39,%40,%41,%42,%43,%44,%45,%46,%47,%48,%49,%50,%51,%52,%53,%54,%55,%56,%57,%58,%59,%60,%61,%62,%63}, "
      "{%64,%65,%66,%67}, %68, p, 1, 1, %70;\n}\n"
      : "+f"(d[0]), "+f"(d[1]), "+f"(d[2]), "+f"(d[3]), "+f"(d[4]), "+f"(d[5]), "+f"(d[6]), "+f"(d[7]),
        "+f"(d[8]), "+f"(d[9]), "+f"(d[10]), "+f"(d[11]), "+f"(d[12]), "+f"(d[13]), "+f"(d[14]), "+f"(d[15]),
        "+f"(d[16]), "+f"(d[17]), "+f"(d[18]), "+f"(d[19]), "+f"(d[20]), "+f"(d[21]), "+f"(d[22]), "+f"(d[23]),
        "+f"(d[24]), "+f"(d[25]), "+f"(d[26]), "+f"(d[27]), "+f"(d[28]), "+f"(d[29]), "+f"(d[30]), "+f"(d[31]),
        "+f"(d[32]), "+f"(d[33]), "+f"(d[34]), "+f"(d[35]), "+f"(d[36]), "+f"(d[37]), "+f"(d[38]), "+f"(d[39]),
        "+f"(d[40]), "+f"(d[41]), "+f"(d[42]), "+f"(d[43]), "+f"(d[44]), "+f"(d[45]), "+f"(d[46]), "+f"(d[47]),
        "+f"(d[48]), "+f"(d[49]), "+f"(d[50]), "+f"(d[51]), "+f"(d[52]), "+f"(d[53]), "+f"(d[54]), "+f"(d[55]),
        "+f"(d[56]), "+f"(d[57]), "+f"(d[58]), "+f"(d[59]), "+f"(d[60]), "+f"(d[61]), "+f"(d[62]), "+f"(d[63])
      : "r"(a[0]), "r"(a[1]), "r"(a[2]), "r"(a[3]), "l"(db), "r"(accum), "n"(TB));
}
template <int N, int TB>
__device__ __forceinline__ void wgmma_rs(float* d, const uint32_t* a, uint64_t db, int accum) {
  if constexpr (N == 16) wgmma_n16<TB>(d, a, db, accum);
  if constexpr (N == 32) wgmma_n32<TB>(d, a, db, accum);
  if constexpr (N == 48) wgmma_n48<TB>(d, a, db, accum);
  if constexpr (N == 64) wgmma_n64<TB>(d, a, db, accum);
  if constexpr (N == 80) wgmma_n80<TB>(d, a, db, accum);
  if constexpr (N == 96) wgmma_n96<TB>(d, a, db, accum);
  if constexpr (N == 112) wgmma_n112<TB>(d, a, db, accum);
  if constexpr (N == 128) wgmma_n128<TB>(d, a, db, accum);
}

struct SsmParams {
  const __nv_bfloat16 *a_re, *a_im, *b_re, *b_im, *c_re, *c_im, *log_dt, *x, *dskip;
  Scratch* g;
};
struct C2 {
  float r, i;
};
__device__ __forceinline__ C2 cmul(C2 a, C2 b) { return {fmaf(a.r, b.r, -a.i * b.i), fmaf(a.r, b.i, a.i * b.r)}; }
__device__ __forceinline__ C2 cmulc(C2 a, C2 b) { return {fmaf(a.r, b.r, a.i * b.i), fmaf(a.i, b.r, -a.r * b.i)}; }
__device__ __forceinline__ C2 cexp_pow(float a2, float rev, float l) {
  float m, t = rev * l, sn, cs;
  asm("ex2.approx.ftz.f32 %0, %1;" : "=f"(m) : "f"(a2 * l));
  t = (t - rintf(t)) * 6.283185307179586f;
  asm("sin.approx.ftz.f32 %0, %1;" : "=f"(sn) : "f"(t));
  asm("cos.approx.ftz.f32 %0, %1;" : "=f"(cs) : "f"(t));
  return {m * cs, m * sn};
}
__device__ __forceinline__ void store8(uint32_t addr, const C2* v) {
  uint32_t re[4], im[4];
#pragma unroll
  for (int i = 0; i < 4; i++) {
    re[i] = pack_bf16(v[2 * i].r, v[2 * i + 1].r);
    im[i] = pack_bf16(v[2 * i].i, v[2 * i + 1].i);
  }
  sts128(addr, re);
  sts128(addr + WS_WARP / 2, im);
}
struct ModeIn {
  uint32_t ar, ai, br, bi, cr, ci, ldt;
};
__device__ __forceinline__ uint32_t ldg16(const __nv_bfloat16* p) {
  uint32_t r;
  asm volatile("ld.global.nc.u16 %0, [%1];" : "=r"(r) : "l"(p));
  return r;
}
__device__ __forceinline__ uint32_t ldg32(const __nv_bfloat16* p) {
  uint32_t r;
  asm volatile("ld.global.nc.u32 %0, [%1];" : "=r"(r) : "l"(p));
  return r;
}
__device__ __forceinline__ ModeIn load_modes(const SsmParams& p, uint32_t d, uint32_t pair) {
  const uint32_t i = d * NMODE + 2 * pair;
  return {ldg32(p.a_re + i), ldg32(p.a_im + i), ldg32(p.b_re + i), ldg32(p.b_im + i),
          ldg32(p.c_re + i), ldg32(p.c_im + i), ldg16(p.log_dt + d)};
}

__device__ __forceinline__ void kgen_modes(uint32_t my, const ModeIn in, uint32_t sel, float (&acc)[6][4]) {
  const int lane = fresh_tid() & 31;
  const uint32_t row = my + lane * 112;
  auto pick = [&](uint32_t v) { return __uint_as_float(__byte_perm(v, 0, sel)); };
  const float dt = round_bf16(__expf(bf_lo(in.ldt)));
  const float a2 = dt * pick(in.ar) * 1.4426950408889634f, rev = dt * pick(in.ai) * 0.15915494309189535f;
  const C2 e1 = cexp_pow(a2, rev, 1.f), e8 = cexp_pow(a2, rev, 8.f), e256 = cexp_pow(a2, rev, 256.f);
  {
    C2 y[8];
    y[0] = {1.f, 0.f};
    y[1] = e8;
    y[2] = cmul(e8, e8);
    y[3] = cmul(y[2], e8);
    y[4] = cmul(y[2], y[2]);
    y[5] = cmul(y[4], y[1]);
    y[6] = cmul(y[4], y[2]);
    y[7] = cmul(y[4], y[3]);
    const C2 e64 = cmul(y[4], y[4]);
    store8(row, y);
#pragma unroll
    for (int c = 1; c < 4; c++) {
#pragma unroll
      for (int i = 0; i < 8; i++) y[i] = (c == 1 && i == 0) ? e64 : cmul(y[i], e64);
      store8(row + 16 * c, y);
    }
  }
  {
    C2 x[8], z[8];
    x[0] = cmulc({pick(in.cr), -pick(in.ci)}, {dt * pick(in.br), dt * pick(in.bi)});
    x[1] = cmulc(x[0], e1);
    const C2 e2 = cmul(e1, e1);
#pragma unroll
    for (int i = 2; i < 8; i++) x[i] = cmulc(x[i - 2], e2);
    store8(row + 64, x);
#pragma unroll
    for (int i = 0; i < 4; i++) z[i] = cmulc(x[2 * i], e256);
    z[4] = cmulc(z[0], e256);
    z[5] = cmulc(z[2], e256);
    z[6] = cmulc(z[4], e256);
    z[7] = cmulc(z[5], e256);
    store8(row + 80, z);
    const C2 e512 = cmul(e256, e256);
    x[0] = cmulc(z[4], e512);
    x[1] = cmulc(z[6], e512);
    x[2] = cmulc(x[0], e512);
    x[3] = cmulc(x[1], e512);
    x[4] = cmulc(x[2], e512);
    x[5] = x[6] = x[7] = {0.f, 0.f};
    store8(row + 96, x);
  }
  __syncwarp();
  const uint32_t aa = my + (lane >> 4) * (WS_WARP / 2) + (lane & 7) * 112 + ((lane >> 3) & 1) * 16;
  const uint32_t ba = my + ((lane >> 3) & 1) * (WS_WARP / 2) + (lane & 7) * 112 + (lane >> 4) * 16 + 64;
#pragma unroll
  for (int ks = 0; ks < 4; ks++) {
    uint32_t a[2][4], b[6];
    ldsm4t(a[0], aa + ks * 896);
    ldsm4t(a[1], aa + ks * 896 + 32);
    ldsm4t(b, ba + ks * 896);
    ldsm2t(b + 4, ba + ks * 896 + 32);
#pragma unroll
    for (int nt = 0; nt < 3; nt++)
#pragma unroll
      for (int mt = 0; mt < 2; mt++) mma_bf16(acc[nt * 2 + mt], a[mt][0], a[mt][1], a[mt][2], a[mt][3], &b[2 * nt]);
  }
  __syncwarp();
}

__device__ __forceinline__ void ld_relaxed128(uint32_t* v, const uint4* p) {
  asm volatile("ld.relaxed.gpu.global.v4.b32 {%0,%1,%2,%3}, [%4];"
               : "=r"(v[0]), "=r"(v[1]), "=r"(v[2]), "=r"(v[3]) : "l"(p) : "memory");
}
__device__ __forceinline__ void stats_load(Scratch* g, uint32_t (&st)[12]) {
  const uint4* sp = &g->stats[fresh_tid()];
#pragma unroll
  for (int e = 0; e < 3; e++) ld_relaxed128(&st[4 * e], sp + 256 * e);
}
__device__ __forceinline__ void kgen_finish(uint32_t sb, Scratch* g, int wg, const float (&acc)[6][4], uint32_t (&st)[12]) {
  const int t = fresh_tid() & 127;
  const uint32_t ws = sb + OFF_WS + wg * WS_BYTES;
  {
    const int lane = t & 31, w = t >> 5;
    const bool up = w & 1;
    float keep[3][4];
#pragma unroll
    for (int k = 0; k < 3; k++) {
      uint32_t send[4];
#pragma unroll
      for (int e = 0; e < 4; e++) {
        send[e] = __float_as_uint(up ? acc[2 * k][e] : acc[2 * k + 1][e]);
        keep[k][e] = up ? acc[2 * k + 1][e] : acc[2 * k][e];
      }
      sts128(ws + w * WS_WARP + k * 512 + lane * 16, send);
      if (wg == 2 && w >= 2) sts128(ws + w * WS_WARP + 1536 + k * 512 + lane * 16, reinterpret_cast<const uint32_t*>(keep[k]));
    }
    if (t < 18 - 8 * (wg & 2))
      sts32(t < 2 ? ws + WS_KC - 4 + t * KC_PITCH : sb + OFF_PK + (2 * wg + ((t - 2) >> 3)) * PK_PITCH + 4 * ((t - 2) & 7), 0);
    wg_bar(wg);
#pragma unroll 1
    for (int n = 0; n < (wg == 2 ? 3 : 1); n++) {
      const uint32_t src = ws + (w ^ (n == 0 ? 1 : n == 1 ? 3 : 2)) * WS_WARP + (n == 2 ? 1536 : 0) + lane * 16;
#pragma unroll
      for (int k = 0; k < 3; k++) {
        uint32_t v[4];
        lds128(v, src + k * 512);
#pragma unroll
        for (int e = 0; e < 4; e++) keep[k][e] += __uint_as_float(v[e]);
      }
    }
    const int q = lane & 3;
    const uint32_t kc = ws + WS_KC + (w >> 1) * KC_PITCH;
#pragma unroll
    for (int h = 0; h < 2; h++) {
      const int j = 16 * up + 8 * h + (lane >> 2);
      const uint32_t p2 = pack_bf16(keep[2][2 * h], keep[2][2 * h + 1]);
      sts32(kc + 2 * (8 * j + 2 * q), pack_bf16(keep[0][2 * h], keep[0][2 * h + 1]));
      sts32(kc + 2 * (q < 2 ? 256 + 4 * j + 2 * q : 256 + 64 * q + 2 * j), pack_bf16(keep[1][2 * h], keep[1][2 * h + 1]));
      if (q < 2 || (q == 2 && j == 0)) sts16(kc + 2 * (512 + 64 * q + j), p2);
      if (q < 2) sts16(kc + 2 * (544 + 64 * q + j), p2 >> 16);
    }
  }
  wg_bar(wg);
  if (wg < 2) stats_load(g, st);
  uint32_t v[2][9];
  const bool dense = t < 64;
#pragma unroll
  for (int ch = 0; ch < 2; ch++) {
    const uint32_t kc = ws + WS_KC + ch * KC_PITCH, k0 = kc + (dense ? 8 * t : 256 + 4 * t);
    v[ch][0] = lds32(k0);
    v[ch][1] = lds32(k0 + 4);
    v[ch][2] = lds16(k0 - (t <= 64 ? 2 : 0));
    v[ch][3] = lds16(kc + 2 * (384 + t));
    v[ch][4] = lds16(kc + 2 * (385 + t));
#pragma unroll
    for (int k = 0; k < 2; k++) {
      v[ch][5 + 2 * k] = lds16(kc + 2 * (512 + 64 * k + (t >> 1)));
      v[ch][6 + 2 * k] = lds16(kc + 2 * (512 + 64 * k + ((t + 1) >> 1)));
    }
  }
  const uint32_t s1 = dense ? 0x1032 : 0x1010, s2 = dense ? 0x7610 : 0x5476, s3 = dense ? 0x1032 : 0x7610;
#pragma unroll
  for (int ch = 0; ch < 2; ch++) {
    if (ch == 1 && wg == 2) break;
    const uint32_t pkb = sb + OFF_PK + (2 * wg + ch) * PK_PITCH + 32 + t * 16;
    uint32_t o[4];
    o[0] = __byte_perm(v[ch][0], v[ch][2], 0x5410);
    o[1] = __byte_perm(v[ch][0], 0, s1);
    o[2] = __byte_perm(v[ch][1], v[ch][0], s2);
    o[3] = __byte_perm(v[ch][1], v[ch][0], s3);
    sts128(pkb, o);
    uint32_t vm = (t & 1) ? v[ch][4] : v[ch][3];
    o[0] = o[1] = __byte_perm(v[ch][3], 0, 0x1010);
    o[2] = __byte_perm(vm, v[ch][3], 0x5410);
    o[3] = __byte_perm(v[ch][4], vm, 0x5410);
    sts128(pkb + 2048, o);
#pragma unroll
    for (int k = 0; k < 2; k++) {
      const uint32_t v0 = v[ch][5 + 2 * k], v1 = v[ch][6 + 2 * k];
      vm = (t & 2) ? v1 : v0;
      o[0] = __byte_perm(vm, v0, 0x5410);
      o[1] = __byte_perm(v1, vm, 0x5410);
      o[2] = o[3] = __byte_perm(v1, 0, 0x1010);
      sts128(pkb + 4096 + 2048 * k, o);
    }
  }
}

__device__ __forceinline__ uint32_t copy_reg(uint32_t v) {
  uint32_t r;
  asm volatile("mov.b32 %0, %1;" : "=r"(r) : "r"(v));
  return r;
}
struct ConvCtx {
  uint32_t pa, pw, pr, ub, xb, dsk;
  uint64_t db;
  uint4* hrow;
  int wg, t;
  uint32_t sig;
};
__device__ __forceinline__ void conv_emit(const ConvCtx& c, int k) {
  uint32_t v[6][4], h[4];
  wg_bar(c.wg);
#pragma unroll
  for (int src = 0; src < 4; src++) lds128(v[src], k == 0 && c.t < src ? c.ub - 64 : c.pr + src * 4080 + 2048 * k);
  lds128(v[4], c.ub + 2048 * k);
  lds128(v[5], c.xb + 2048 * k);
#pragma unroll
  for (int e = 0; e < 4; e++) {
    const uint32_t y = add_bf16x2(add_bf16x2(v[0][e], v[1][e]), add_bf16x2(v[2][e], v[3][e]));
    h[e] = add_bf16x2(v[5][e], add_bf16x2(y, mul_bf16x2(v[4][e], c.dsk)));
  }
  c.hrow[128 * k] = make_uint4(h[0], h[1], h[2], h[3]);
}
__device__ __forceinline__ void conv_spill(const ConvCtx& c, const float* acc, int b) {
  uint32_t p[4];
#pragma unroll
  for (int e = 0; e < 4; e++) p[e] = pack_bf16(acc[2 * e], acc[2 * e + 1]);
  asm volatile("stmatrix.sync.aligned.m8n8.x4.trans.shared.b16 [%0], {%1,%2,%3,%4};"
               ::"r"(c.pw + b * 512), "r"(p[0]), "r"(p[1]), "r"(p[2]), "r"(p[3]) : "memory");
}
template <int B>
__device__ __forceinline__ void conv_batches(const ConvCtx& c, float (&acc)[64], uint32_t (&a)[2][4][4]) {
  constexpr int N = (B + 1) & 1;
  WG_FENCE();
#pragma unroll
  for (int k = 0; k < 4; k++) wgmma_rs<128 - 16 * B, 0>(acc + 8 * B, a[B & 1][k], c.db - 16 * (k >> 1) - 4 * (k & 1), B + k);
  WG_COMMIT();
  if constexpr (B < 7) {
#pragma unroll
    for (int k = 0; k < 4; k++) {
      const uint32_t o = c.pa + 1024 * (B + 1) + 512 * (k >> 1) + 128 * (k & 1);
      a[N][k][0] = lds32(o);
      a[N][k][1] = lds32(o + 256);
    }
  }
  if constexpr (B == 0) wg_bar(c.wg);
  if constexpr (B > 0) conv_spill(c, acc + 8 * (B - 1), B - 1);
  if constexpr (B == 4) {
    conv_emit(c, 0);
    __syncwarp();
    if (c.sig) mbar_arrive(c.sig);
  }
  WG_WAIT(0);
#pragma unroll
  for (int i = 8 * B; i < 64; i++) asm volatile("mov.b32 %0, %1;" : "=f"(acc[i]) : "f"(acc[i]));
  if constexpr (B < 7) {
#pragma unroll
    for (int k = 0; k < 4; k++) {
      a[N][k][2] = copy_reg(k < 2 ? a[B & 1][k + 2][1] : a[N][k - 2][1]);
      a[N][k][3] = copy_reg(a[N][k][0]);
    }
    conv_batches<B + 1>(c, acc, a);
  }
}

__device__ __forceinline__ void conv_task(uint32_t sb, Scratch* g, int wg, int w, int local, int d, bool last) {
  const int t = fresh_tid() & 127, lane = t & 31;
  const uint32_t ub = sb + OFF_U + local * U_PITCH + U_PAD, part = sb + OFF_PART + wg * SLOT;
  ConvCtx c;
  c.pa = sb + OFF_PK + local * PK_PITCH + 32 + 4 * (8 * w + (lane >> 2) - 2 * (lane & 3));
  c.pw = part + w * 4096 + lane * 16;
  c.pr = part + 16 * t;
  c.ub = ub + 16 * t;
  c.xb = sb + OFF_X + local * X_PITCH + 16 * t;
  c.db = (uint64_t)((ub & 0x3FFFF) >> 4) | ((uint64_t)(128 >> 4) << 16) | ((uint64_t)(256 >> 4) << 32);
  c.hrow = reinterpret_cast<uint4*>(g->hT + d * L) + t;
  c.wg = wg;
  c.t = t;
  c.sig = last && lane == 0 ? sb + B_CV : 0;
  float acc[64];
  uint32_t a[2][4][4];
#pragma unroll
  for (int k = 0; k < 4; k++) {
    const uint32_t o = c.pa + 512 * (k >> 1) + 128 * (k & 1);
    a[0][k][0] = lds32(o);
    a[0][k][1] = lds32(o + 256);
    a[0][k][2] = copy_reg(k < 2 ? 0 : a[0][k & 1][1]);
    a[0][k][3] = copy_reg(a[0][k][0]);
  }
  if (wg < 2 && !last) asm volatile("bar.sync 4, 256;" ::: "memory");
  c.dsk = lds32(sb + OFF_DSK + 4 * local);
  conv_batches<0>(c, acc, a);
  conv_spill(c, acc + 56, 7);
  conv_emit(c, 1);
}

__device__ __forceinline__ void mma_k8(float* c, uint32_t a0, uint32_t a1, uint32_t b) {
  asm volatile("mma.sync.aligned.m16n8k8.row.col.f32.bf16.bf16.f32 {%0,%1,%2,%3}, {%4,%5}, {%6}, {%0,%1,%2,%3};"
               : "+f"(c[0]), "+f"(c[1]), "+f"(c[2]), "+f"(c[3]) : "r"(a0), "r"(a1), "r"(b));
}

__device__ __forceinline__ void ln1_stats(uint32_t sb, Scratch* g, int c, const uint4 (&xv)[9]) {
  const int t = fresh_tid() & 127, lane = t & 31;
  float st[5][4];
#pragma unroll
  for (int i = 0; i < 5; i++) st[i][0] = st[i][1] = st[i][2] = st[i][3] = 0.f;
  const uint32_t ones[2] = {0x3f803f80u, 0x3f803f80u};
#pragma unroll
  for (int i = 0; i < 9; i++) {
    mma_bf16(st[0], xv[i].x, xv[i].y, xv[i].z, xv[i].w, ones);
    mma_k8(st[1], xv[i].x, xv[i].y, xv[i].x);
    mma_k8(st[2], xv[i].x, xv[i].y, xv[i].y);
    mma_k8(st[3], xv[i].z, xv[i].w, xv[i].z);
    mma_k8(st[4], xv[i].z, xv[i].w, xv[i].w);
  }
  float s = st[0][0] + st[0][2];
  float q = (lane & 4) ? (st[1][1] + st[3][1]) + (st[2][3] + st[4][3]) : (st[1][0] + st[3][0]) + (st[2][2] + st[4][2]);
  s += __shfl_xor_sync(~0u, s, 4);
  q += __shfl_xor_sync(~0u, q, 4);
  q = __shfl_sync(~0u, q, (lane & 24) + (lane >> 3));
  const float m = s * (1.f / D), r = ln_rstd(fmaxf(q * (1.f / D) - m * m, 0.f));
  const int sub = t & 7;
  const uint32_t b = pack_bf16(sub == 0 ? m : sub == 1 ? r : r - round_bf16(r), 0.f);
  if (sub < 3) sts16(sb + OFF_RES8 + sub * 32 + (t >> 3) * 2, b ? b : 0x8000u);
  wg_bar(2);
  if (t < 6) {
    uint32_t v[4];
    lds128(v, sb + OFF_RES8 + t * 16);
    asm volatile("st.relaxed.gpu.global.v4.b32 [%0], {%1,%2,%3,%4};" ::"l"(&g->stats[(t >> 1) * 256 + 2 * c + (t & 1)]),
                 "r"(v[0]), "r"(v[1]), "r"(v[2]), "r"(v[3]) : "memory");
  }
}

__device__ __forceinline__ void x_transpose(uint32_t sb, int c, int w) {
  const int lane = fresh_tid() & 31, rank = c & 1;
  uint32_t dx[2];
#pragma unroll
  for (int hf = 0; hf < 2; hf++) {
    const int rel = 8 * hf + (lane >> 2) - ((c >> 1) & 7), loc = rel > 4 ? rel - 5 : rel;
    dx[hf] = (rel > 4) == rank ? OFF_X + loc * X_PITCH + 2048 * rank : OFF_STG + loc * STG_PITCH;
    dx[hf] = rel >= 0 && rel < 9 ? sb + dx[hf] + 16 * (lane & 3) + 64 * w : 0;
  }
#pragma unroll 1
  for (int half = 0; half < 2; half++) {
    mbar_wait(sb + B_G + 8 * half, 0);
    uint32_t x[8][4];
#pragma unroll
    for (int i = 0; i < 8; i++)
      ldsm4t(x[i], sb + OFF_G + (16 * half + 4 * (i >> 1) + w) * 1024 + lane * 32 + (((i ^ (lane >> 2)) & 1) << 4));
#pragma unroll
    for (int i = 0; i < 8; i++)
      if (dx[i & 1]) sts128(dx[i & 1] + 1024 * half + 256 * (i >> 1), x[i]);
  }
  asm volatile("fence.proxy.async.shared::cta;" ::: "memory");
  wg_bar(2);
  if (elect_one()) {
    const uint32_t pb = mapa(sb, rank ^ 1), dst = pb + OFF_X + 2048 * rank;
    bulk_peer(dst + w * X_PITCH, sb + OFF_STG + w * STG_PITCH, 2048, pb + B_UX);
    if (w == 0) bulk_peer(dst + 4 * X_PITCH, sb + OFF_STG + 4 * STG_PITCH, 2048, pb + B_UX);
    if (w == 1) mbar_arrive(sb + B_XL);
  }
  __syncwarp();
}

__device__ __forceinline__ void ln1_apply(uint32_t sb, Scratch* g, uint32_t bar, uint32_t (&st)[12]) {
  const int t = fresh_tid();
  const uint32_t ok = mbar_test(bar);
  for (uint32_t spins = 0;; spins++) {
    uint32_t mn = ~0u;
#pragma unroll
    for (int e = 0; e < 12; e++) mn = min(mn, st[e]);
    if (__all_sync(~0u, mn != 0)) break;
    if (spins > SPIN_LIMIT) __trap();
    stats_load(g, st);
  }
  if (!ok) mbar_wait(bar, 0);
  uint32_t x[5][4];
#pragma unroll
  for (int ch = 0; ch < 5; ch++) lds128(x[ch], sb + OFF_X + ch * X_PITCH + 16 * t);
#pragma unroll
  for (int ch = 0; ch < 5; ch++) {
#pragma unroll
    for (int e = 0; e < 4; e++) {
      const uint32_t dv = sub_bf16x2(x[ch][e], st[e]);
      x[ch][e] = fma_bf16x2(dv, st[4 + e], mul_bf16x2(dv, st[8 + e]));
    }
    sts128(sb + OFF_U + ch * U_PITCH + U_PAD + 16 * t, x[ch]);
  }
}

struct Ring {
  uint32_t slot, phase;
  __device__ __forceinline__ uint32_t off() const { return slot * SLOT; }
  __device__ __forceinline__ void next() {
    if (++slot == NS) { slot = 0; phase ^= 1; }
  }
};

__device__ __forceinline__ uint64_t bdesc(uint32_t addr) {
  return (uint64_t)((addr & 0x3FFFF) >> 4) | ((uint64_t)(BOX >> 4) << 16) | ((uint64_t)(1024 >> 4) << 32) | (1ull << 62);
}
__device__ __forceinline__ void release_slot(uint32_t sb, uint32_t slot, int lane) {
  if (lane == 0) mbar_arrive(sb + B_EMPTY + 8 * slot);
}
__device__ __forceinline__ void stage_partial(const float* acc, uint32_t addr) {
#pragma unroll
  for (int j = 0; j < 4; j++) {
    uint32_t p[4];
#pragma unroll
    for (int i = 0; i < 4; i++) p[i] = pack_bf16(acc[8 * j + 2 * i], acc[8 * j + 2 * i + 1]);
    sts128(addr + j * 512, p);
  }
}
__device__ __forceinline__ void stage_done(uint32_t bar, int lane) {
  asm volatile("fence.proxy.async.shared::cta;" ::: "memory");
  __syncwarp();
  if (lane == 0) mbar_arrive(bar);
}
__device__ __forceinline__ void lds128_if(uint32_t* r, uint32_t a, bool on) {
  asm volatile("{\n.reg .pred p;\nsetp.ne.u32 p, %5, 0;\n@p ld.shared.v4.b32 {%0,%1,%2,%3}, [%4];\n}\n"
               : "+r"(r[0]), "+r"(r[1]), "+r"(r[2]), "+r"(r[3]) : "r"(a), "r"((uint32_t)on) : "memory");
}
__device__ __forceinline__ void stage_sum(const float* acc, const uint32_t* add, uint32_t addr) {
#pragma unroll
  for (int j = 0; j < 4; j++) {
    uint32_t p[4];
#pragma unroll
    for (int i = 0; i < 4; i++) p[i] = add_bf16x2(add[4 * j + i], pack_bf16(acc[8 * j + 2 * i], acc[8 * j + 2 * i + 1]));
    sts128(addr + j * 512, p);
  }
}
__device__ __forceinline__ void center_rest(uint32_t* a, uint32_t m0, uint32_t m1, int step) {
  asm volatile(
      "{\n.reg .pred p;\nsetp.ne.s32 p, %130, 0;\n@p bra.uni SKIP;\n"
      "sub.rn.bf16x2 %0,%0,%128;\nsub.rn.bf16x2 %1,%1,%129;\nsub.rn.bf16x2 %2,%2,%128;\nsub.rn.bf16x2 %3,%3,%129;\n"
      "sub.rn.bf16x2 %4,%4,%128;\nsub.rn.bf16x2 %5,%5,%129;\nsub.rn.bf16x2 %6,%6,%128;\nsub.rn.bf16x2 %7,%7,%129;\n"
      "sub.rn.bf16x2 %8,%8,%128;\nsub.rn.bf16x2 %9,%9,%129;\nsub.rn.bf16x2 %10,%10,%128;\nsub.rn.bf16x2 %11,%11,%129;\n"
      "sub.rn.bf16x2 %12,%12,%128;\nsub.rn.bf16x2 %13,%13,%129;\nsub.rn.bf16x2 %14,%14,%128;\nsub.rn.bf16x2 %15,%15,%129;\n"
      "sub.rn.bf16x2 %16,%16,%128;\nsub.rn.bf16x2 %17,%17,%129;\nsub.rn.bf16x2 %18,%18,%128;\nsub.rn.bf16x2 %19,%19,%129;\n"
      "sub.rn.bf16x2 %20,%20,%128;\nsub.rn.bf16x2 %21,%21,%129;\nsub.rn.bf16x2 %22,%22,%128;\nsub.rn.bf16x2 %23,%23,%129;\n"
      "sub.rn.bf16x2 %24,%24,%128;\nsub.rn.bf16x2 %25,%25,%129;\nsub.rn.bf16x2 %26,%26,%128;\nsub.rn.bf16x2 %27,%27,%129;\n"
      "sub.rn.bf16x2 %28,%28,%128;\nsub.rn.bf16x2 %29,%29,%129;\nsub.rn.bf16x2 %30,%30,%128;\nsub.rn.bf16x2 %31,%31,%129;\n"
      "sub.rn.bf16x2 %32,%32,%128;\nsub.rn.bf16x2 %33,%33,%129;\nsub.rn.bf16x2 %34,%34,%128;\nsub.rn.bf16x2 %35,%35,%129;\n"
      "sub.rn.bf16x2 %36,%36,%128;\nsub.rn.bf16x2 %37,%37,%129;\nsub.rn.bf16x2 %38,%38,%128;\nsub.rn.bf16x2 %39,%39,%129;\n"
      "sub.rn.bf16x2 %40,%40,%128;\nsub.rn.bf16x2 %41,%41,%129;\nsub.rn.bf16x2 %42,%42,%128;\nsub.rn.bf16x2 %43,%43,%129;\n"
      "sub.rn.bf16x2 %44,%44,%128;\nsub.rn.bf16x2 %45,%45,%129;\nsub.rn.bf16x2 %46,%46,%128;\nsub.rn.bf16x2 %47,%47,%129;\n"
      "sub.rn.bf16x2 %48,%48,%128;\nsub.rn.bf16x2 %49,%49,%129;\nsub.rn.bf16x2 %50,%50,%128;\nsub.rn.bf16x2 %51,%51,%129;\n"
      "sub.rn.bf16x2 %52,%52,%128;\nsub.rn.bf16x2 %53,%53,%129;\nsub.rn.bf16x2 %54,%54,%128;\nsub.rn.bf16x2 %55,%55,%129;\n"
      "sub.rn.bf16x2 %56,%56,%128;\nsub.rn.bf16x2 %57,%57,%129;\nsub.rn.bf16x2 %58,%58,%128;\nsub.rn.bf16x2 %59,%59,%129;\n"
      "sub.rn.bf16x2 %60,%60,%128;\nsub.rn.bf16x2 %61,%61,%129;\nsub.rn.bf16x2 %62,%62,%128;\nsub.rn.bf16x2 %63,%63,%129;\n"
      "sub.rn.bf16x2 %64,%64,%128;\nsub.rn.bf16x2 %65,%65,%129;\nsub.rn.bf16x2 %66,%66,%128;\nsub.rn.bf16x2 %67,%67,%129;\n"
      "sub.rn.bf16x2 %68,%68,%128;\nsub.rn.bf16x2 %69,%69,%129;\nsub.rn.bf16x2 %70,%70,%128;\nsub.rn.bf16x2 %71,%71,%129;\n"
      "sub.rn.bf16x2 %72,%72,%128;\nsub.rn.bf16x2 %73,%73,%129;\nsub.rn.bf16x2 %74,%74,%128;\nsub.rn.bf16x2 %75,%75,%129;\n"
      "sub.rn.bf16x2 %76,%76,%128;\nsub.rn.bf16x2 %77,%77,%129;\nsub.rn.bf16x2 %78,%78,%128;\nsub.rn.bf16x2 %79,%79,%129;\n"
      "sub.rn.bf16x2 %80,%80,%128;\nsub.rn.bf16x2 %81,%81,%129;\nsub.rn.bf16x2 %82,%82,%128;\nsub.rn.bf16x2 %83,%83,%129;\n"
      "sub.rn.bf16x2 %84,%84,%128;\nsub.rn.bf16x2 %85,%85,%129;\nsub.rn.bf16x2 %86,%86,%128;\nsub.rn.bf16x2 %87,%87,%129;\n"
      "sub.rn.bf16x2 %88,%88,%128;\nsub.rn.bf16x2 %89,%89,%129;\nsub.rn.bf16x2 %90,%90,%128;\nsub.rn.bf16x2 %91,%91,%129;\n"
      "sub.rn.bf16x2 %92,%92,%128;\nsub.rn.bf16x2 %93,%93,%129;\nsub.rn.bf16x2 %94,%94,%128;\nsub.rn.bf16x2 %95,%95,%129;\n"
      "sub.rn.bf16x2 %96,%96,%128;\nsub.rn.bf16x2 %97,%97,%129;\nsub.rn.bf16x2 %98,%98,%128;\nsub.rn.bf16x2 %99,%99,%129;\n"
      "sub.rn.bf16x2 %100,%100,%128;\nsub.rn.bf16x2 %101,%101,%129;\nsub.rn.bf16x2 %102,%102,%128;\nsub.rn.bf16x2 %103,%103,%129;\n"
      "sub.rn.bf16x2 %104,%104,%128;\nsub.rn.bf16x2 %105,%105,%129;\nsub.rn.bf16x2 %106,%106,%128;\nsub.rn.bf16x2 %107,%107,%129;\n"
      "sub.rn.bf16x2 %108,%108,%128;\nsub.rn.bf16x2 %109,%109,%129;\nsub.rn.bf16x2 %110,%110,%128;\nsub.rn.bf16x2 %111,%111,%129;\n"
      "sub.rn.bf16x2 %112,%112,%128;\nsub.rn.bf16x2 %113,%113,%129;\nsub.rn.bf16x2 %114,%114,%128;\nsub.rn.bf16x2 %115,%115,%129;\n"
      "sub.rn.bf16x2 %116,%116,%128;\nsub.rn.bf16x2 %117,%117,%129;\nsub.rn.bf16x2 %118,%118,%128;\nsub.rn.bf16x2 %119,%119,%129;\n"
      "sub.rn.bf16x2 %120,%120,%128;\nsub.rn.bf16x2 %121,%121,%129;\nsub.rn.bf16x2 %122,%122,%128;\nsub.rn.bf16x2 %123,%123,%129;\n"
      "sub.rn.bf16x2 %124,%124,%128;\nsub.rn.bf16x2 %125,%125,%129;\nsub.rn.bf16x2 %126,%126,%128;\nsub.rn.bf16x2 %127,%127,%129;\n"
      "SKIP:\n}\n"
      : "+r"(a[16]), "+r"(a[17]), "+r"(a[18]), "+r"(a[19]), "+r"(a[20]), "+r"(a[21]), "+r"(a[22]), "+r"(a[23]),
        "+r"(a[24]), "+r"(a[25]), "+r"(a[26]), "+r"(a[27]), "+r"(a[28]), "+r"(a[29]), "+r"(a[30]), "+r"(a[31]),
        "+r"(a[32]), "+r"(a[33]), "+r"(a[34]), "+r"(a[35]), "+r"(a[36]), "+r"(a[37]), "+r"(a[38]), "+r"(a[39]),
        "+r"(a[40]), "+r"(a[41]), "+r"(a[42]), "+r"(a[43]), "+r"(a[44]), "+r"(a[45]), "+r"(a[46]), "+r"(a[47]),
        "+r"(a[48]), "+r"(a[49]), "+r"(a[50]), "+r"(a[51]), "+r"(a[52]), "+r"(a[53]), "+r"(a[54]), "+r"(a[55]),
        "+r"(a[56]), "+r"(a[57]), "+r"(a[58]), "+r"(a[59]), "+r"(a[60]), "+r"(a[61]), "+r"(a[62]), "+r"(a[63]),
        "+r"(a[64]), "+r"(a[65]), "+r"(a[66]), "+r"(a[67]), "+r"(a[68]), "+r"(a[69]), "+r"(a[70]), "+r"(a[71]),
        "+r"(a[72]), "+r"(a[73]), "+r"(a[74]), "+r"(a[75]), "+r"(a[76]), "+r"(a[77]), "+r"(a[78]), "+r"(a[79]),
        "+r"(a[80]), "+r"(a[81]), "+r"(a[82]), "+r"(a[83]), "+r"(a[84]), "+r"(a[85]), "+r"(a[86]), "+r"(a[87]),
        "+r"(a[88]), "+r"(a[89]), "+r"(a[90]), "+r"(a[91]), "+r"(a[92]), "+r"(a[93]), "+r"(a[94]), "+r"(a[95]),
        "+r"(a[96]), "+r"(a[97]), "+r"(a[98]), "+r"(a[99]), "+r"(a[100]), "+r"(a[101]), "+r"(a[102]), "+r"(a[103]),
        "+r"(a[104]), "+r"(a[105]), "+r"(a[106]), "+r"(a[107]), "+r"(a[108]), "+r"(a[109]), "+r"(a[110]), "+r"(a[111]),
        "+r"(a[112]), "+r"(a[113]), "+r"(a[114]), "+r"(a[115]), "+r"(a[116]), "+r"(a[117]), "+r"(a[118]), "+r"(a[119]),
        "+r"(a[120]), "+r"(a[121]), "+r"(a[122]), "+r"(a[123]), "+r"(a[124]), "+r"(a[125]), "+r"(a[126]), "+r"(a[127]),
        "+r"(a[128]), "+r"(a[129]), "+r"(a[130]), "+r"(a[131]), "+r"(a[132]), "+r"(a[133]), "+r"(a[134]), "+r"(a[135]),
        "+r"(a[136]), "+r"(a[137]), "+r"(a[138]), "+r"(a[139]), "+r"(a[140]), "+r"(a[141]), "+r"(a[142]), "+r"(a[143])
      : "r"(m0), "r"(m1), "r"(step));
}
__device__ __forceinline__ void lag_sync(int wg) {
  if (wg == 1) asm volatile("bar.sync 4, 256;" ::: "memory");
}
__device__ __forceinline__ void lag_arrive(int wg) {
  if (wg == 0) asm volatile("bar.arrive 4, 256;" ::: "memory");
}

__device__ __forceinline__ void add_packed(uint32_t* d, uint32_t a0, uint32_t a1) {
#pragma unroll
  for (int j = 0; j < 4; j++) {
    uint32_t v[4];
    lds128(d + 4 * j, a0 + j * 512);
    lds128(v, a1 + j * 512);
#pragma unroll
    for (int i = 0; i < 4; i++) d[4 * j + i] = add_bf16x2(d[4 * j + i], v[i]);
  }
}

template <int T, typename Fn>
__device__ __forceinline__ void step64(float (&acc)[32], const uint32_t (&A)[144], uint32_t sb, uint64_t desc0, Ring& ring,
                                       int wg, int lane, Fn&& side) {
  uint32_t prev = 0;
  ring.slot = __shfl_sync(~0u, ring.slot, 0);
#pragma unroll
  for (int st = 0; st < 5; st++) {
    mbar_wait(sb + B_FULL + 8 * ring.slot, ring.phase);
    const uint64_t db = desc0 + (ring.off() >> 4);
    if (st == 5 - LAG3) lag_sync(wg);
    WG_FENCE();
#pragma unroll
    for (int k = 0; k < (st < 4 ? 8 : 4); k++) wgmma_rs<64, 1>(acc, &A[(st * 8 + k) * 4], db + k * 128, st + k);
    WG_COMMIT();
    if (st == 4) lag_arrive(wg);
    if (st > 0 && T * 5 + st - 1 < 15 - NS) {
      WG_WAIT(1);
      release_slot(sb, prev, lane);
    }
    prev = ring.slot;
    ring.next();
    side(st);
  }
  WG_WAIT(0);
  if (T * 5 + 4 < 15 - NS) release_slot(sb, prev, lane);
}

__device__ __forceinline__ void ffn_consumer(uint32_t sb, Scratch* g, int warp, int r, int s, __nv_bfloat16* __restrict__ out) {
  const int tid = fresh_tid(), wg = warp >> 2, w = warp & 3, lane = tid & 31;
  const uint32_t stash = OFF_STASH + wg * STASH_STRIDE;
  const uint32_t priv = sb + stash + w * 2048 + lane * 16;
  uint32_t A[144];
  float rs0, rs1;
  uint32_t mm0, mm1;
  const uint32_t tr_off = ((lane >> 4) * 8 + (lane & 7)) * 128 + (((2 * w + ((lane >> 3) & 1)) ^ (lane & 7)) << 4);
  {
    float st[4][4];
#pragma unroll
    for (int i = 0; i < 4; i++) st[i][0] = st[i][1] = st[i][2] = st[i][3] = 0.f;
    const uint32_t ones[2] = {0x3f803f80u, 0x3f803f80u};
    const bool up = s & 1;
    uint32_t ok = 0;
#pragma unroll
    for (int gi = 0; gi < 6; gi++) {
      if (gi < 5) {
        if (!ok) mbar_wait(sb + B_H + 8 * (wg * 5 + gi), 0);
#pragma unroll
        for (int j = 0; j < 8; j++) {
          const int k = 8 * gi - 4 + j;
          if (k >= 0) ldsm4t(&A[4 * k], sb + (gi ? stash - BOX : (NS - 1) * SLOT + wg * BOX) + tr_off + k * 2048);
        }
        if (gi < 4) ok = mbar_test(sb + B_H + 8 * (wg * 5 + gi + 1));
      }
      if (gi > 0) {
#pragma unroll
        for (int j = 0; j < 8; j++) {
          const int k = 8 * gi - 12 + j;
          if (k < 0) continue;
          const uint32_t* a = &A[4 * k];
          const uint32_t bt[2] = {up ? a[1] : a[0], up ? a[3] : a[2]};
          mma_bf16(st[k & 1], a[0], a[1], a[2], a[3], ones);
          mma_bf16(st[2 + (k & 1)], a[0], a[1], a[2], a[3], bt);
        }
      }
      if (gi == 2) release_slot(sb, NS - 1, lane);
    }
    const float m0 = (st[0][0] + st[1][0]) * (1.f / D), m1 = (st[0][2] + st[1][2]) * (1.f / D);
    const float qe = up ? st[2][2] + st[3][2] : st[2][0] + st[3][0], qo = up ? st[2][3] + st[3][3] : st[2][1] + st[3][1];
    const float q = __shfl_sync(~0u, (lane & 4) ? qo : qe, (lane & 28) + (lane >> 3)), m = up ? m1 : m0;
    if (wg == 1) asm volatile("bar.arrive 6, 256;" ::: "memory");
    rs0 = rs1 = ln_rstd(fmaxf(q * (1.f / D) - m * m, 0.f));
    if ((lane & 3) == 0) {
      const uint32_t pb = mapa(sb, up ^ 1);
      asm volatile("st.async.weak.shared::cluster.mbarrier::complete_tx::bytes.b32 [%0], %1, [%2];"
                   ::"r"(pb + OFF_VAR + 32 * warp + lane), "r"(__float_as_uint(rs0)), "r"(pb + B_VAR + 8 * wg) : "memory");
    }
    if (warp == s) {
#pragma unroll
      for (int j = 0; j < 4; j++) sts128(sb + OFF_RES8 + j * 512 + lane * 16, &A[128 + 4 * j]);
    }
    mm0 = pack_bf16(m0, m0);
    mm1 = pack_bf16(m1, m1);
#pragma unroll
    for (int i = 0; i < 16; i++) A[i] = sub_bf16x2(A[i], (i & 1) ? mm1 : mm0);
  }

  Ring ring{0, 0};
  uint32_t full = 0;
  const uint64_t desc0 = bdesc(sb);
#pragma unroll 1
  for (int step = 0; step < 12; step++) {
    float acc[64];
    uint32_t prev = 0;
#pragma unroll
    for (int kb = 0; kb < 9; kb++) {
      if (kb > 0 || !full) mbar_wait(sb + B_FULL + 8 * ring.slot, ring.phase);
      const uint64_t db = desc0 + (ring.off() >> 4);
      if (kb == SKB && step == 0 && wg == 0) asm volatile("bar.sync 6, 256;" ::: "memory");
      if (kb == 9 - LAG) lag_sync(wg);
      WG_FENCE();
#pragma unroll
      for (int k = 0; k < 4; k++) wgmma_rs<128, 1>(acc, &A[(kb * 4 + k) * 4], db + k * 128, kb + k);
      WG_COMMIT();
      if (kb == 0) center_rest(A, mm0, mm1, step);
      if (kb == RKB) {
#pragma unroll
        for (int j = 0; j < 4; j++) lds128_if(&A[128 + 4 * j], priv + j * 512, step == 9);
      }
      if (kb == 8) lag_arrive(wg);
      if (kb == 0 && step > 9) stage_done(sb + B_SF + 8 * (wg * 5 + step - 10), lane);
      if (kb > 0) {
        WG_WAIT(1);
        release_slot(sb, prev, lane);
#pragma unroll
        for (int j = 0; j < 4; j++) lds128_if(&A[16 * (kb - 1) + 4 * j], priv + (kb - 1) * BOX + j * 512, step == 8);
      }
      if (kb == VKB && step == 0) {
        mbar_wait(sb + B_VAR + 8 * wg, 0);
        wg_bar(wg);
        const float rpeer = __uint_as_float(lds32(sb + OFF_VAR + 32 * warp + (lane & 28)));
        if (s & 1) rs0 = rpeer;
        else rs1 = rpeer;
        if (warp == s && (lane & 3) == 0) {
          sts32(sb + OFF_RS + lane, __float_as_uint(rs0));
          sts32(sb + OFF_RS + 32 + lane, __float_as_uint(rs1));
        }
      }
      prev = ring.slot;
      ring.next();
    }
    if (step > 9) {
      mbar_wait(sb + B_XIN + 8 * (wg * 4 + step - 10), 0);
      mbar_wait(sb + B_SE + 8 * (wg * 3 + step - 10), 0);
    }
    full = mbar_test(sb + B_FULL + 8 * ring.slot, ring.phase);
    WG_WAIT(0);
    release_slot(sb, prev, lane);
    if (step < 9) {
      uint32_t hp[16];
      const float c0 = 0.5f * rs0, c1 = 0.5f * rs1;
#pragma unroll
      for (int i = 0; i < 16; i++) {
        const float c = (i & 1) ? c1 : c0;
        const float g0 = acc[2 * i] * c, g1 = acc[2 * i + 1] * c;
        const float h0 = fmaf(g0, tanh_hw(g0), g0) * acc[32 + 2 * i];
        const float h1 = fmaf(g1, tanh_hw(g1), g1) * acc[33 + 2 * i];
        hp[i] = pack_bf16(h0, h1);
      }
#pragma unroll
      for (int j = 0; j < 4; j++) sts128(priv + (step & 7) * BOX + j * 512, &hp[4 * j]);
    } else {
      const int e = step - 9;
      stage_partial(acc, priv + (2 + (e & 1)) * BOX);
      uint32_t xin[16];
#pragma unroll
      for (int j = 0; j < 4; j++) lds128(&xin[4 * j], e > 0 ? priv + ((e - 1) & 1) * BOX + j * 512 : sb + OFF_ZERO);
      stage_sum(acc + 32, xin, priv + 4 * BOX);
    }
  }

  float acc[32];
  uint32_t pa[16], o8[2], ok;
  step64<0>(acc, A, sb, desc0, ring, wg, lane, [&](int st) {
    if (st == 0) stage_done(sb + B_SF + 8 * (wg * 5 + 2), lane);
    if (st == 3) ok = mbar_test(sb + B_XIN + 8 * (wg * 4 + 2));
    if (st == 4) {
      if (!ok) mbar_wait(sb + B_XIN + 8 * (wg * 4 + 2), 0);
#pragma unroll
      for (int j = 0; j < 4; j++) lds128(&pa[4 * j], priv + j * 512);
    }
  });
#pragma unroll
  for (int j = 0; j < 4; j++) {
    uint32_t p[4];
#pragma unroll
    for (int i = 0; i < 4; i++) p[i] = ~add_bf16x2(pa[4 * j + i], pack_bf16(acc[8 * j + 2 * i], acc[8 * j + 2 * i + 1]));
    sts128(priv + j * 512, p);
  }
  stage_done(sb + B_SF + 8 * (wg * 5 + 3), lane);
  step64<1>(acc, A, sb, desc0, ring, wg, lane, [&](int st) {
    if (st == B8ST) {
      const int t = fresh_tid();
      mbar_wait(sb + B_B8, 0);
      float v[4] = {0.f, 0.f, 0.f, 0.f};
#pragma unroll
      for (int i = 0; i < 8; i++) {
        uint32_t q[2];
        lds64(q, sb + OFF_STASH + (i >> 2) * STASH_STRIDE + 6 * BOX + (i & 3) * 2048 + 8 * t);
        v[0] += bf_lo(q[0]); v[1] += bf_hi(q[0]);
        v[2] += bf_lo(q[1]); v[3] += bf_hi(q[1]);
      }
      uint32_t h[2];
      lds64(h, sb + OFF_RES8 + 8 * t);
      const uint32_t ra = sb + OFF_RS + ((t >> 1) & 28);
      const float r0 = __uint_as_float(lds32(ra)), r1 = __uint_as_float(lds32(ra + 32));
      o8[0] = pack_bf16(fmaf(v[0], r0, bf_lo(h[0])), fmaf(v[1], r0, bf_hi(h[0])));
      o8[1] = pack_bf16(fmaf(v[2], r1, bf_lo(h[1])), fmaf(v[3], r1, bf_hi(h[1])));
      stage_done(sb + B_CV + 16, lane);
    }
  });
  stage_partial(acc, priv + 3 * BOX);
  stage_done(sb + B_SF + 8 * (wg * 5 + 4), lane);
  step64<2>(acc, A, sb, desc0, ring, wg, lane, [&](int st) {
    if (st == 1) {
      const int t = fresh_tid(), row = (s >> 2) * 1024 + r * 64 + (s & 3) * 16 + ((t >> 3) & 7);
      uint32_t* o = reinterpret_cast<uint32_t*>(out + row * D + 512 + 16 * (t >> 6) + 8 * (t & 1) + (t & 6));
      o[0] = o8[0];
      o[4 * D] = o8[1];
    }
    const uint4* src = &g->last[((r * 8 + s) * 8 + warp) * 128 + lane];
    if (st == LLST) {
#pragma unroll
      for (int j = 0; j < 4; j++) ld_relaxed128(&pa[4 * j], src + 32 * j);
    }
    if (st == 3) ok = mbar_test(sb + B_LIN + 8 * wg) & mbar_test(sb + B_XIN + 8 * (wg * 4 + 3));
    if (st == 4) {
      uint32_t pb[16];
      if (!ok) {
        mbar_wait(sb + B_LIN + 8 * wg, 0);
        mbar_wait(sb + B_XIN + 8 * (wg * 4 + 3), 0);
      }
      add_packed(pb, priv + 5 * BOX, priv + 6 * BOX);
      for (uint32_t spins = 0;; spins++) {
        uint32_t mn = ~0u;
#pragma unroll
        for (int i = 0; i < 16; i++) mn = min(mn, pa[i]);
        if (__all_sync(~0u, mn != 0)) break;
        if (spins > SPIN_LIMIT) __trap();
#pragma unroll
        for (int j = 0; j < 4; j++) ld_relaxed128(&pa[4 * j], src + 32 * j);
      }
#pragma unroll
      for (int j = 0; j < 4; j++) {
        uint32_t v[4];
        lds128(v, priv + BOX + j * 512);
#pragma unroll
        for (int i = 0; i < 4; i++) pa[4 * j + i] = add_bf16x2(add_bf16x2(~pa[4 * j + i], v[i]), pb[4 * j + i]);
      }
    }
  });
  const uint32_t ob = sb + stash + 5 * BOX + w * 2048;
  __syncwarp();
#pragma unroll
  for (int i = 0; i < 4; i++) {
    uint32_t p[4];
    ldsm4t(p, sb + stash + 7 * BOX + tr_off + i * 2048);
#pragma unroll
    for (int j = 0; j < 4; j++) {
      const float rr = (j & 1) ? rs1 : rs0;
      const float lo = acc[8 * i + 2 * j] + bf_lo(pa[4 * i + j]), hi = acc[8 * i + 2 * j + 1] + bf_hi(pa[4 * i + j]);
      p[j] = add_bf16x2(p[j], pack_bf16(lo * rr, hi * rr));
    }
    stsm4(ob + (lane & 15) * 128 + (((2 * i + (lane >> 4)) ^ (lane & 7)) << 4), p);
  }
  __syncwarp();
  __nv_bfloat16* o = out + (wg * 1024 + r * 64 + w * 16 + (lane >> 3)) * D + s * 64 + (lane & 7) * 8;
#pragma unroll
  for (int i = 0; i < 4; i++) {
    const int row = 4 * i + (lane >> 3);
    uint32_t v[4];
    lds128(v, ob + row * 128 + (((lane & 7) ^ (row & 7)) << 4));
    *reinterpret_cast<uint4*>(o + 4 * i * D) = make_uint4(v[0], v[1], v[2], v[3]);
  }
}

struct StageSrc {
  const CUtensorMap *m0, *m1;
  int x0, x1, y0, y1;
};
__device__ __forceinline__ StageSrc stage_src(int it, int s, const CUtensorMap* w1, const CUtensorMap* w3,
                                              const CUtensorMap* w2) {
  if (it < 108) {
    const int step = it / 9, kb = it - step * 9, e = step - 9;
    if (it < 81) return {w1, w3, s * 576 + step * 64, s * 576 + step * 64, kb * 64, kb * 64};
    return {w2, w2, (((s + 2 * e + 2) & 7) ^ 1) * 64, (e == 0 ? 8 : (s + 2 * e) & 7) * 64, s * 576 + kb * 64, s * 576 + kb * 64};
  }
  const int e = (it - 108) / 5, st = it - 108 - e * 5, x = (e == 0 ? (s + 6) & 7 : e == 1 ? s ^ 1 : s) * 64;
  return {w2, st < 4 ? w2 : nullptr, x, x, s * 576 + st * 128, s * 576 + st * 128 + 64};
}
__device__ __forceinline__ void prefetch_box(const CUtensorMap* m, int x, int y) {
  asm volatile("cp.async.bulk.prefetch.tensor.2d.L2.global [%0, {%1, %2}];" ::"l"(m), "r"(x), "r"(y) : "memory");
}

__device__ __forceinline__ void ffn_producer(uint32_t sb, int r, int s, int first, const CUtensorMap* w1,
                                             const CUtensorMap* w3, const CUtensorMap* w2) {
  Ring ring{(uint32_t)first, 1};
  mbar_wait(sb + B_CV + 8, 0);
  int it = first, pf = first + PFN + ((r - first - PFN) & 7);
#pragma unroll 1
  while (it < 123) {
    StageSrc a = stage_src(it, s, w1, w3, w2);
    const int dy = it < 108 ? 64 : 128, last = it < 108 ? -1 : it + 4, end = it < 9 ? 9 : it + (it < 108 ? 9 : 5);
#pragma unroll 1
    for (; it < end; it++) {
      const uint32_t bar = sb + B_FULL + 8 * ring.slot, dst = sb + ring.off();
      mbar_wait(sb + B_EMPTY + 8 * ring.slot, ring.slot == NS - 1 ? ring.phase ^ 1 : ring.phase);
      if (elect_one()) {
        mbar_expect(bar, it != last ? SLOT : BOX);
        tma2d(dst, a.m0, a.x0, a.y0, bar);
        if (it != last) tma2d(dst + BOX, a.m1, a.x1, a.y1, bar);
      }
      __syncwarp();
      if (it + PFN == pf) {
        if (elect_one()) {
          const StageSrc b = stage_src(pf, s, w1, w3, w2);
          if (r < 8) prefetch_box(b.m0, b.x0, b.y0);
          else if (b.m1) prefetch_box(b.m1, b.x1, b.y1);
        }
        __syncwarp();
        pf += pf < 115 ? 8 : 1000;
      }
      a.y0 += dy;
      a.y1 += dy;
      ring.next();
    }
  }
  const uint32_t pb = mapa(sb, (s & 1) ^ 1);
#pragma unroll 1
  for (int wg = 0; wg < 2; wg++) {
    const uint32_t stash = OFF_STASH + wg * STASH_STRIDE;
    mbar_wait(sb + B_SF + 8 * (wg * 5 + 4), 0);
    if (elect_one()) bulk_peer(pb + stash + BOX, sb + stash + 3 * BOX, BOX, pb + B_XIN + 8 * (wg * 4 + 3));
    __syncwarp();
  }
}

__device__ __forceinline__ void ffn_sender(uint32_t sb, Scratch* g, int r, int s, int wg) {
  const uint32_t stash = OFF_STASH + wg * STASH_STRIDE, pb = mapa(sb, (s & 1) ^ 1);
  mbar_wait(sb + B_CV + 8 * wg, 0);
  if (elect_one()) {
    asm volatile("fence.release.gpu;" ::: "memory");
    red_add(&g->epoch[32 * wg], 1);
  }
  __syncwarp();
#pragma unroll 1
  for (int e = 0; e < 3; e++) {
    mbar_wait(sb + B_SF + 8 * (wg * 5 + e), 0);
    if (e == 0) {
      if (elect_one()) mbar_arrive_cluster(pb + B_PRDY + 8 * wg);
      __syncwarp();
      mbar_wait(sb + B_PRDY + 8 * wg, 0);
    }
    if (elect_one()) {
      bulk_peer(pb + stash + (e & 1) * BOX, sb + stash + (2 + (e & 1)) * BOX, BOX, pb + B_XIN + 8 * (wg * 4 + e));
      const int idx = ((r * 8 + ((s + 2 * e) & 7)) * 2 + e - 1) * 2 + wg;
      uint4* dst = e == 0 ? &g->part8[((r * 8 + s) * 2 + wg) * 512] : &g->part[idx * 512];
#pragma unroll 1
      for (uint32_t q = 0; q < BOX; q += PACE) {
        bulk_store(dst + (q >> 4), sb + stash + 4 * BOX + q, PACE);
        asm volatile("cp.async.bulk.commit_group;" ::: "memory");
        asm volatile("cp.async.bulk.wait_group.read 0;" ::: "memory");
      }
      mbar_arrive(sb + B_SE + 8 * (wg * 3 + e));
      asm volatile("cp.async.bulk.wait_group 0;" ::: "memory");
      asm volatile("fence.release.gpu;" ::: "memory");
      if (e == 0) {
#pragma unroll
        for (int q = 0; q < 4; q++) red_add(&g->flag8[(r * 8 + wg * 4 + q) * 32], 1);
      } else {
        red_add(&g->flag[idx], 1);
      }
    }
    __syncwarp();
  }
  mbar_wait(sb + B_XIN + 8 * (wg * 4 + 3), 0);
  if (elect_one()) mbar_arrive_cluster(pb + B_DONE + 8 * wg);
  __syncwarp();
  mbar_wait(sb + B_DONE + 8 * wg, 0);
}

__device__ __forceinline__ void load_res(uint32_t sb, const CUtensorMap* ht, int r, int s) {
  if (elect_one()) {
    tma2d(sb + OFF_STASH + 7 * BOX, ht, r * 64, s * 64, sb + B_LIN);
    tma2d(sb + OFF_STASH + STASH_STRIDE + 7 * BOX, ht, 1024 + r * 64, s * 64, sb + B_LIN + 8);
  }
  __syncwarp();
}
__device__ __forceinline__ void ffn_receiver(uint32_t sb, Scratch* g, int c, int r, int s, const CUtensorMap* ht,
                                             const CUtensorMap* ht2) {
  const int lane = fresh_tid() & 31;
  mbar_wait(sb + B_CV + 8, 0);
#pragma unroll 1
  for (int h = 0; h < 2; h++) {
    wait_flag(&g->epoch[32 * h], (lds32(sb + OFF_DSK + 32) & ~127u) + 128);
    if (elect_one()) {
      asm volatile("fence.proxy.async.global;" ::: "memory");
      tma2d(sb + (NS - 1) * SLOT + h * BOX, ht, h * 1024 + r * 64, 0, sb + B_H + 40 * h);
#pragma unroll
      for (int i = 0; i < 4; i++)
        tma2d(sb + OFF_STASH + h * STASH_STRIDE + i * SLOT, ht2, h * 1024 + r * 64, 64 + 128 * i, sb + B_H + 40 * h + 8 + 8 * i);
    }
    __syncwarp();
  }
  if (lane < 6) g->stats[(lane >> 1) * 256 + 2 * c + (lane & 1)] = make_uint4(0, 0, 0, 0);
  mbar_wait(sb + B_SF, 0);
  mbar_wait(sb + B_SF + 40, 0);
  wait_flag(&g->flag8[(r * 8 + s) * 32], 8);
  __syncwarp();
  if (elect_one()) {
    g->flag8[(r * 8 + s) * 32] = 0;
    asm volatile("fence.proxy.async.global;" ::: "memory");
#pragma unroll 1
    for (int i = 0; i < 8; i++)
      bulk_load(sb + OFF_STASH + (i >> 2) * STASH_STRIDE + 6 * BOX + (i & 3) * 2048, &g->part8[(r * 8 + i) * 1024 + s * 128],
                2048, sb + B_B8);
  }
  __syncwarp();
  const int base = (r * 8 + s) * 4;
#pragma unroll 1
  for (int late = 0; late < 2; late++) {
    if (late) {
#pragma unroll 1
      for (int wg = 0; wg < 2; wg++) {
        mbar_wait(sb + B_SF + 8 * (wg * 5 + 3), 0);
        if (elect_one()) {
          asm volatile("fence.proxy.async.global;" ::: "memory");
#pragma unroll 1
          for (uint32_t q = 0; q < BOX; q += PACE3) {
            asm volatile("cp.reduce.async.bulk.global.shared::cta.bulk_group.or.b32 [%0], [%1], %2;"
                         ::"l"(&g->last[((r * 8 + ((s + 6) & 7)) * 2 + wg) * 512 + (q >> 4)]),
                         "r"(sb + OFF_STASH + wg * STASH_STRIDE + q), "r"(PACE3) : "memory");
            asm volatile("cp.async.bulk.commit_group;" ::: "memory");
            asm volatile("cp.async.bulk.wait_group.read 0;" ::: "memory");
          }
        }
        __syncwarp();
      }
      mbar_wait(sb + B_CV + 16, 0);
      load_res(sb, ht, r, s);
    }
    uint32_t todo = late ? 0x0c : 0x03;
#pragma unroll 1
    for (uint32_t spins = 0; todo; spins++) {
      if (spins > SPIN_LIMIT) __trap();
      uint32_t ready = __ballot_sync(~0u, ((todo >> lane) & 1) && ld_acquire(&g->flag[base + lane]) != 0);
      __syncwarp();
      todo &= ~ready;
#pragma unroll 1
      for (; ready; ready &= ready - 1) {
        const int i = __ffs(ready) - 1, wg = i & 1, j = i >> 1;
        if (elect_one()) {
          asm volatile("fence.proxy.async.global;" ::: "memory");
          bulk_load(sb + OFF_STASH + wg * STASH_STRIDE + (5 + j) * BOX, &g->part[(base + i) * 512], BOX,
                    sb + B_LIN + 8 * wg);
        }
        __syncwarp();
      }
    }
  }
  if (lane < 4) g->flag[base + lane] = 0;
}

template <uint32_t B0, uint32_t B1>
__device__ __forceinline__ void init_barriers(uint32_t sb) {
#pragma unroll
  for (uint32_t b = B0; b < B1; b += 8) mbar_init(sb + b, b < B_SF ? 1 : b < B_EMPTY ? 4 : 8);
#pragma unroll
  for (uint32_t b = B0; b < B1 && b < B_FULL; b += 8)
    mbar_expect(sb + b, b < B_PK    ? 2 * BOX
                        : b < B_LIN ? BOX
                        : b < B_H   ? 3 * BOX
                        : b < B_UX  ? ((b - B_H) % 40 ? 2 : 1) * BOX
                        : b < B_VAR ? 5 * L
                        : b < B_B8  ? 128
                                    : 2 * BOX);
}

__global__ void __launch_bounds__(384, 1)
fused_kernel(const __grid_constant__ SsmParams p, __nv_bfloat16* __restrict__ out,
             const __grid_constant__ CUtensorMap tm_w1, const __grid_constant__ CUtensorMap tm_w3,
             const __grid_constant__ CUtensorMap tm_w2, const __grid_constant__ CUtensorMap tm_ht,
             const __grid_constant__ CUtensorMap tm_ht2, const __grid_constant__ CUtensorMap tm_x) {
  extern __shared__ __align__(1024) uint8_t smem[];
  uint32_t t0;
  asm volatile("mov.u32 %0, %clock;" : "=r"(t0));
  const ModeIn in = load_modes(
      p, 9 * (blockIdx.x >> 1) + (threadIdx.x < 256 ? 5 * (blockIdx.x & 1) + (threadIdx.x >> 6) : 4), threadIdx.x & 63);
  uint32_t sb = (uint32_t)__cvta_generic_to_shared(smem);
  asm volatile("" : "+r"(sb));
  const int c = blockIdx.x, cl = c >> 1, rank = c & 1, tid = threadIdx.x, warp = warp_index(), wg = warp >> 2;
  const int s = ((cl & 1) * 2 + ((cl >> 3) & 1)) * 2 + rank, r = ((cl >> 1) & 3) * 4 + (cl >> 4);
  Scratch* const g = p.g;
  unsigned target = 0;
  const int w = warp & 3, lane = tid & 31;
  const int ch0 = 9 * cl + 5 * rank;
  uint4 xv[9];
  if (wg == 2) {
    const uint4* xr = reinterpret_cast<const uint4*>(p.x) + (16 * c + ((tid & 127) >> 3)) * (D / 8) + (tid & 7);
    for (uint32_t now = t0; now - t0 < XDELAY;) asm volatile("mov.u32 %0, %clock;" : "=r"(now));
#pragma unroll
    for (int i = 0; i < 9; i++)
      asm volatile("ld.global.nc.v4.u32 {%0,%1,%2,%3}, [%4];"
                   : "=r"(xv[i].x), "=r"(xv[i].y), "=r"(xv[i].z), "=r"(xv[i].w) : "l"(xr + 8 * i));
  }
  const uint32_t dsk = ldg16(p.dskip + min(ch0 + (tid & 7), D - 1));
  if (tid == 8) asm volatile("ld.relaxed.gpu.global.u32 %0, [%1];" : "=r"(target) : "l"(&g->epoch[32]) : "memory");
  if (warp == 9) {
    const uint32_t z[4] = {0, 0, 0, 0};
    sts128(sb + OFF_ZERO, z);
#pragma unroll 1
    for (int i = 0; i < 5; i++)
      if (lane < (i < 4 ? 24 : 26))
        sts128(sb + (lane < 24 ? OFF_U + i * U_PITCH : OFF_PK - U_PAD + i * PK_PITCH) + lane * 16, z);
  }
  if (warp == 10 && elect_one()) {
    init_barriers<B_PK, B_END>(sb);
    asm volatile("fence.mbarrier_init.release.cluster;" ::: "memory");
  }
  if (warp == 8 && elect_one()) {
    asm volatile("prefetch.tensormap [%0];" ::"l"(&tm_x) : "memory");
    init_barriers<B_G, B_PK>(sb);
    asm volatile("fence.mbarrier_init.release.cluster;" ::: "memory");
#pragma unroll
    for (int i = 0; i < 2; i++)
      asm volatile(
          "cp.async.bulk.tensor.5d.shared::cluster.global.mbarrier::complete_tx::bytes [%0], [%1, {%3, %4, %4, %4, %5}], [%2];"
          ::"r"(sb + OFF_G + i * SLOT), "l"(&tm_x), "r"(sb + B_G + 8 * i), "r"((9 * cl) & ~7), "r"(0), "r"(32 * rank + 16 * i)
          : "memory");
  }
  __syncwarp();
  asm volatile("barrier.cluster.arrive.relaxed.aligned;" ::: "memory");
  if (wg == 2) {
    ln1_stats(sb, g, c, xv);
    asm volatile("barrier.cluster.wait.aligned;" ::: "memory");
    x_transpose(sb, c, w);
  }
  const int ntask = wg < 2 ? 2 : 1 - rank;
  if (wg < 2 || rank == 1) {
    float acc[6][4];
#pragma unroll
    for (int i = 0; i < 6; i++) acc[i][0] = acc[i][1] = acc[i][2] = acc[i][3] = 0.f;
#pragma unroll 1
    for (int k = wg >> 1; k < 2; k++) {
      kgen_modes(sb + OFF_WS + wg * WS_BYTES + w * WS_WARP, in, (wg == 2 ? w >> 1 : k) ? 0x3244 : 0x1044, acc);
    }
    uint32_t st[12];
    if (wg < 2) asm volatile("barrier.cluster.wait.aligned;" ::: "memory");
    kgen_finish(sb, g, wg, acc, st);
    if (wg < 2) {
      wg_bar(wg);
      if (tid < 9) sts32(sb + OFF_DSK + 4 * tid, tid < 8 ? dsk * 0x10001u : target);
      ln1_apply(sb, g, sb + (wg == rank ? B_XL : B_UX), st);
      asm volatile("fence.proxy.async.shared::cta;\nbar.arrive 6, 384;" ::: "memory");
    } else {
      asm volatile("fence.proxy.async.shared::cta;" ::: "memory");
      wg_bar(2);
      if (w == 2 && elect_one()) {
        const uint32_t pb = mapa(sb, 0), off = OFF_PK + 4 * PK_PITCH + 32;
        bulk_peer(pb + off, sb + off, BOX, pb + B_PK);
      }
      __syncwarp();
    }
  }
  if (wg == 2) {
    asm volatile("bar.sync 6, 384;" ::: "memory");
    mbar_wait(sb + B_UX, 0);
    if (w == 0 && elect_one()) {
#pragma unroll 1
      for (int i = 0; i < EARLY; i++) {
        const uint32_t bar = sb + B_FULL + 8 * i, dst = sb + i * SLOT;
        mbar_expect(bar, SLOT);
        tma2d(dst, &tm_w1, s * 576, i * 64, bar);
        tma2d(dst + BOX, &tm_w3, s * 576, i * 64, bar);
      }
      asm volatile("prefetch.tensormap [%0];" ::"l"(&tm_ht) : "memory");
      asm volatile("prefetch.tensormap [%0];" ::"l"(&tm_ht2) : "memory");
    }
    if (w == 1 && elect_one()) {
#pragma unroll 1
      for (int i = EARLY + ((r - EARLY) & 7); i < EARLY + PFN; i += 8)
        prefetch_box(r < 8 ? &tm_w1 : &tm_w3, s * 576 + (i / 9) * 64, (i % 9) * 64);
    }
    __syncwarp();
#pragma unroll
    for (int i = 0; i < 8; i++) g->last[(r * 8 + s) * 1024 + i * 128 + (tid & 127)] = make_uint4(0, 0, 0, 0);
  }
#pragma unroll 1
  for (int k = 0; k < ntask; k++) {
    const int local = wg == 2 ? 3 : 2 * wg + k + (wg & k & (rank ^ 1));
    if (local == 4) mbar_wait(sb + B_PK, 0);
    conv_task(sb, g, wg, w, local, ch0 + local, k);
  }
  asm volatile("fence.proxy.async.shared::cta;" ::: "memory");
  __syncwarp();
  if (wg == 2) wg_bar(2);
  else if (elect_one()) mbar_arrive(sb + B_CV + 8);
  __syncwarp();

  if (wg < 2) {
    asm volatile("setmaxnreg.inc.sync.aligned.u32 240;");
    ffn_consumer(sb, g, warp, r, s, out);
  } else {
    asm volatile("setmaxnreg.dec.sync.aligned.u32 24;");
    const int hw = warp & 3;
    if (hw == 0) ffn_producer(sb, r, s, EARLY, &tm_w1, &tm_w3, &tm_w2);
    else if (hw < 3) ffn_sender(sb, g, r, s, hw - 1);
    else ffn_receiver(sb, g, c, r, s, &tm_ht, &tm_ht2);
  }
}

typedef CUresult (*EncodeFn)(CUtensorMap*, CUtensorMapDataType, cuuint32_t, void*, const cuuint64_t*, const cuuint64_t*,
                             const cuuint32_t*, const cuuint32_t*, CUtensorMapInterleave, CUtensorMapSwizzle,
                             CUtensorMapL2promotion, CUtensorMapFloatOOBfill);

void make_map(EncodeFn enc, CUtensorMap* m, void* p, uint64_t cols, uint64_t rows, uint32_t box_rows = 64) {
  cuuint64_t dims[2] = {cols, rows}, strides[1] = {cols * 2};
  cuuint32_t box[2] = {64, box_rows}, es[2] = {1, 1};
  enc(m, CU_TENSOR_MAP_DATA_TYPE_BFLOAT16, 2, p, dims, strides, box, es, CU_TENSOR_MAP_INTERLEAVE_NONE,
      CU_TENSOR_MAP_SWIZZLE_128B, CU_TENSOR_MAP_L2_PROMOTION_L2_128B, CU_TENSOR_MAP_FLOAT_OOB_FILL_NONE);
}

}

extern "C" void kernel_launch(void* const* d_in, const int* in_sizes, int n_in, void* d_out, int out_size) {
  typedef const __nv_bfloat16* P;
  void* fn = nullptr;
  cudaDriverEntryPointQueryResult qr;
  cudaGetDriverEntryPoint("cuTensorMapEncodeTiled", &fn, cudaEnableDefault, &qr);
  EncodeFn enc = (EncodeFn)fn;
  void* hT = nullptr;
  cudaGetSymbolAddress(&hT, g_scratch);
  CUtensorMap m1, m3, m2, mh, mh2, mx;
  make_map(enc, &m1, d_in[10], F, D);
  make_map(enc, &m3, d_in[11], F, D);
  make_map(enc, &m2, d_in[12], D, F);
  make_map(enc, &mh, hT, L, D);
  make_map(enc, &mh2, hT, L, D, 128);
  {
    cuuint64_t dims[5] = {D, 2, 4, 4, 64}, strides[4] = {D * 2, D * 16, D * 4, D * 64};
    cuuint32_t box[5] = {16, 2, 4, 4, 16}, es[5] = {1, 1, 1, 1, 1};
    enc(&mx, CU_TENSOR_MAP_DATA_TYPE_BFLOAT16, 5, d_in[0], dims, strides, box, es, CU_TENSOR_MAP_INTERLEAVE_NONE,
        CU_TENSOR_MAP_SWIZZLE_32B, CU_TENSOR_MAP_L2_PROMOTION_L2_128B, CU_TENSOR_MAP_FLOAT_OOB_FILL_NONE);
  }
  SsmParams p = {(P)d_in[1], (P)d_in[2], (P)d_in[3], (P)d_in[4], (P)d_in[5], (P)d_in[6],
                 (P)d_in[7], (P)d_in[0], (P)d_in[8], (Scratch*)hT};
  cudaFuncSetAttribute(fused_kernel, cudaFuncAttributeMaxDynamicSharedMemorySize, SMEM_BYTES);
  cudaLaunchConfig_t cfg = {};
  cfg.gridDim = dim3(128);
  cfg.blockDim = dim3(384);
  cfg.dynamicSmemBytes = SMEM_BYTES;
  cfg.stream = cudaStreamPerThread;
  cudaLaunchAttribute at[1];
  at[0].id = cudaLaunchAttributeClusterDimension;
  at[0].val.clusterDim.x = 2;
  at[0].val.clusterDim.y = 1;
  at[0].val.clusterDim.z = 1;
  cfg.attrs = at;
  cfg.numAttrs = 1;
  cudaLaunchKernelEx(&cfg, fused_kernel, p, (__nv_bfloat16*)d_out, m1, m3, m2, mh, mh2, mx);
}
```
